```python
import torch

def _softmax(x, axis=-1):
    return torch.softmax(x, dim=axis)

def _gelu(x):
    return torch.nn.functional.gelu(x, approximate='tanh')

def _silu(x):
    return torch.nn.functional.silu(x)

def _sigmoid(x):
    return torch.sigmoid(x)

def _layernorm(x, axis=-1, eps=1e-05):
    m = x.mean(dim=axis, keepdim=True)
    v = x.var(dim=axis, keepdim=True, unbiased=False)
    return (x - m) / torch.sqrt(v + eps)

def _scatter_add(tgt, idx, src, axis=0):
    return tgt.clone().index_add_(axis, idx, src)

def _segment_sum(src, seg, n):
    out = torch.zeros((n,) + src.shape[1:], dtype=src.dtype)
    return out.index_add_(0, seg, src)

def _pad(x, pw):
    flat = tuple((v for pair in reversed(pw) for v in pair))
    return torch.nn.functional.pad(x, flat)
kernel_name = 'concat_heads__sliding_local_dilated__memory_aug_recurrent_mem_tr__prompt'

def setup_inputs():

    _w = lambda a: (lambda t: t.to(torch.bfloat16) if t.is_floating_point() else t)(torch.as_tensor(a))

    def _A_setup():
        B, S, D = (1, 2048, 640)
        return {'x': _w((lambda *s: torch.randn(*s, dtype=torch.bfloat16) * 0.2)(B, S, D)), 'wqkv': _w((lambda *s: torch.randn(*s, dtype=torch.bfloat16) * 0.2)(D, 3 * D)), 'wo': _w((lambda *s: torch.randn(*s, dtype=torch.bfloat16) * 0.05)(D, D))}
    _A_in = _A_setup()

    def _B_setup():
        B, S, Dm = (1, 2048, 640)
        H, Dh = (32, 192)
        M, seg = (8, 32)
        seg = min(seg, S)
        S = S // seg * seg
        return {'x': _w((lambda *s: torch.randn(*s, dtype=torch.bfloat16) * 0.05)(B, S, Dm)), 'mem0': _w((lambda *s: torch.randn(*s, dtype=torch.bfloat16) * 1.6)(B, M, Dm)), 'Wq': _w((lambda *s: torch.randn(*s, dtype=torch.bfloat16) * 0.8)(Dm, H, Dh) * Dm ** (-0.5)), 'Wk': _w((lambda *s: torch.randn(*s, dtype=torch.bfloat16) * 0.8)(Dm, H, Dh) * Dm ** (-0.5)), 'Wv': _w((lambda *s: torch.randn(*s, dtype=torch.bfloat16) * 1.6)(Dm, H, Dh) * Dm ** (-0.5)), 'Wo': _w((lambda *s: torch.randn(*s, dtype=torch.bfloat16) * 1.6)(H, Dh, Dm) * (H * Dh) ** (-0.5)), 'seg_len': seg}
    _B_in = _B_setup()
    return {'A_x': _A_in['x'], 'A_wqkv': _A_in['wqkv'], 'A_wo': _A_in['wo'], 'B_x': _B_in['x'], 'B_mem0': _B_in['mem0'], 'B_Wq': _B_in['Wq'], 'B_Wk': _B_in['Wk'], 'B_Wv': _B_in['Wv'], 'B_Wo': _B_in['Wo'], 'B_seg_len': _B_in['seg_len']}

def reference(A_x, A_wqkv, A_wo, B_x, B_mem0, B_Wq, B_Wk, B_Wv, B_Wo, B_seg_len):

    def _A_ref(x, wqkv, wo):
        B, S, D = x.shape
        H = 32
        Dh = D // H
        W, dil = (8, 2)
        qkv = (lambda x, *d: x.permute(*d))((x @ wqkv).reshape(B, S, 3, H, Dh), 2, 0, 3, 1, 4)
        q, k, v = (qkv[0], qkv[1], qkv[2])
        scale = Dh ** (-0.5)
        pos = torch.arange(S)
        off = torch.arange(W) * dil
        idx = pos[:, None] - off[None, :]
        mask = idx >= 0
        idx_c = torch.where(mask, idx, 0).reshape(-1)
        kg = k[:, :, idx_c, :].reshape(B, H, S, W, Dh)
        vg = v[:, :, idx_c, :].reshape(B, H, S, W, Dh)
        logits = torch.einsum('bhsd,bhswd->bhsw', q, kg) * scale
        logits = torch.where(mask[None, None, :, :], logits, -1000000000.0)
        attn = _softmax(logits, axis=-1)
        o = torch.einsum('bhsw,bhswd->bhsd', attn, vg)
        return (lambda x, *d: x.permute(*d))(o, 0, 2, 1, 3).reshape(B, S, D) @ wo

    def _B_ref(x, mem0, Wq, Wk, Wv, Wo, seg_len):
        B, S, Dm = x.shape
        H, Dh = (Wq.shape[1], Wq.shape[2])
        M = mem0.shape[1]
        scale = Dh ** (-0.5)
        n_seg = S // seg_len
        L = M + seg_len
        idx = torch.arange(L)
        mask = (idx[:, None] < M) | (idx[:, None] >= idx[None, :])
        mem = mem0
        outs = []
        for s in range(n_seg):
            xs = x[:, s * seg_len:(s + 1) * seg_len, :].clone()
            h = torch.concatenate([mem, xs], axis=1)
            q = torch.einsum('btd,dhe->bhte', h, Wq)
            k = torch.einsum('btd,dhe->bhte', h, Wk)
            v = torch.einsum('btd,dhe->bhte', h, Wv)
            scores = torch.einsum('bhqe,bhke->bhqk', q, k) * scale
            scores = torch.where(mask[None, None], scores, -1000000000.0)
            p = _softmax(scores, axis=-1)
            o = torch.einsum('bhqk,bhke->bhqe', p, v)
            o = torch.einsum('bhte,hed->btd', o, Wo)
            mem = o[:, :M, :].clone()
            outs.append(o[:, M:, :])
        return torch.concatenate(outs, axis=1)
    a = _A_ref(A_x, A_wqkv, A_wo)
    b = _B_ref(B_x, B_mem0, B_Wq, B_Wk, B_Wv, B_Wo, B_seg_len)
    return torch.concatenate([a, b], axis=-1)
```

```cpp
#include <cuda_runtime.h>
#include <cuda_bf16.h>
#include <cuda.h>
#include <stdint.h>
#include <string.h>
#include <math.h>
#include <type_traits>

typedef __nv_bfloat16 bf16;

constexpr int SEQ = 2048, DM = 640, NH = 32, DH = 192, HE = NH * DH;
constexpr int NSEG = 64;
constexpr int OUTW = 1280;

__device__ uint4 g_xch[(4 << 20) / 16];
__device__ uint4 g_near4[96 * 2];
__device__ bf16  g_ox[SEQ * HE];
__device__ bf16  g_qkvA[SEQ * 3 * DM];
__device__ bf16  g_oA[SEQ * DM];
__device__ uint4 g_vx[96 * NSEG * 256];
__device__ uint4 g_op[NSEG * 70 * 256];
__device__ uint4 g_tail[2 * 32 * 80 * 32];
__device__ uint32_t g_epoch;
__device__ uint32_t g_flagv[96 * 64];
__device__ uint32_t g_prog[96];
__device__ uint32_t g_cnt[256];
constexpr int CNT_Q = 0, CNT_ATT = 8, CNT_O = 16, SPIN_LIM = 1 << 15;

__device__ __forceinline__ uint32_t smem_u32(const void* p) { return (uint32_t)__cvta_generic_to_shared(p); }
__device__ __forceinline__ uint32_t pack2(float lo, float hi) {
    uint32_t r; asm("cvt.rn.bf16x2.f32 %0, %1, %2;" : "=r"(r) : "f"(hi), "f"(lo)); return r;
}
__device__ __forceinline__ float ex2(float x) { float r; asm("ex2.approx.ftz.f32 %0, %1;" : "=f"(r) : "f"(x)); return r; }
__device__ __forceinline__ float rcpf(float x) { float r; asm("rcp.approx.ftz.f32 %0, %1;" : "=f"(r) : "f"(x)); return r; }
__device__ __forceinline__ void mbar_init(uint32_t bar, uint32_t cnt) {
    asm volatile("mbarrier.init.shared::cta.b64 [%0], %1;" :: "r"(bar), "r"(cnt) : "memory");
}
__device__ __forceinline__ void mbar_arrive(uint32_t bar) {
    asm volatile("mbarrier.arrive.shared::cta.b64 _, [%0];" :: "r"(bar) : "memory");
}
__device__ __forceinline__ void mbar_expect(uint32_t bar, uint32_t bytes) {
    asm volatile("mbarrier.arrive.expect_tx.shared::cta.b64 _, [%0], %1;" :: "r"(bar), "r"(bytes) : "memory");
}
constexpr int WAIT_LIM = 2048;
template <int N> __device__ __forceinline__ void mbar_wait_n(uint32_t bar, uint32_t parity) {
    asm volatile("{.reg .pred p, q; .reg .u32 c; mov.u32 c, %2;\n"
                 "WL_%=: sub.u32 c, c, 1; setp.eq.u32 q, c, 0; @q bra WD_%=; mbarrier.try_wait.parity.shared::cta.b64 p, [%0], %1;\n"
                 "@!p bra WL_%=; WD_%=: }" :: "r"(bar), "r"(parity), "n"(N) : "memory");
}
__device__ __forceinline__ void mbar_wait(uint32_t bar, uint32_t parity) { mbar_wait_n<1024>(bar, parity); }
__device__ __forceinline__ void mbar_wait_long(uint32_t bar, uint32_t parity) { mbar_wait_n<4096>(bar, parity); }
__device__ __forceinline__ void bar_sync(int id, int n) { asm volatile("bar.sync %0, %1;" :: "r"(id), "r"(n) : "memory"); }
__device__ __forceinline__ void bar_arrive(int id, int n) { asm volatile("bar.arrive %0, %1;" :: "r"(id), "r"(n) : "memory"); }
__device__ __forceinline__ void tma2d(uint32_t dst, const CUtensorMap* tm, int c0, int c1, uint32_t bar) {
    asm volatile("cp.async.bulk.tensor.2d.shared::cluster.global.mbarrier::complete_tx::bytes [%0], [%1, {%3, %4}], [%2];"
                 :: "r"(dst), "l"(tm), "r"(bar), "r"(c0), "r"(c1) : "memory");
}
__device__ __forceinline__ void tma_st(const CUtensorMap* tm, uint32_t src, int c0, int c1) {
    asm volatile("cp.async.bulk.tensor.2d.global.shared::cta.bulk_group [%0, {%2, %3}], [%1];" :: "l"(tm), "r"(src), "r"(c0), "r"(c1) : "memory");
}
__device__ __forceinline__ void ldsm4(uint32_t a, uint32_t& r0, uint32_t& r1, uint32_t& r2, uint32_t& r3) {
    asm volatile("ldmatrix.sync.aligned.m8n8.x4.shared.b16 {%0,%1,%2,%3}, [%4];"
                 : "=r"(r0), "=r"(r1), "=r"(r2), "=r"(r3) : "r"(a) : "memory");
}
__device__ __forceinline__ void ldsm4t(uint32_t a, uint32_t& r0, uint32_t& r1, uint32_t& r2, uint32_t& r3) {
    asm volatile("ldmatrix.sync.aligned.m8n8.x4.trans.shared.b16 {%0,%1,%2,%3}, [%4];"
                 : "=r"(r0), "=r"(r1), "=r"(r2), "=r"(r3) : "r"(a) : "memory");
}
__device__ __forceinline__ void ldsm2t(uint32_t a, uint32_t& r0, uint32_t& r1) {
    asm volatile("ldmatrix.sync.aligned.m8n8.x2.trans.shared.b16 {%0,%1}, [%2];" : "=r"(r0), "=r"(r1) : "r"(a) : "memory");
}
__device__ __forceinline__ void stsm4t(uint32_t a, uint32_t r0, uint32_t r1, uint32_t r2, uint32_t r3) {
    asm volatile("stmatrix.sync.aligned.m8n8.x4.trans.shared.b16 [%0], {%1,%2,%3,%4};"
                 :: "r"(a), "r"(r0), "r"(r1), "r"(r2), "r"(r3) : "memory");
}
__device__ __forceinline__ void stsm4(uint32_t a, uint32_t r0, uint32_t r1, uint32_t r2, uint32_t r3) {
    asm volatile("stmatrix.sync.aligned.m8n8.x4.shared.b16 [%0], {%1,%2,%3,%4};"
                 :: "r"(a), "r"(r0), "r"(r1), "r"(r2), "r"(r3) : "memory");
}
__device__ __forceinline__ void stsm2t(uint32_t a, uint32_t r0, uint32_t r1) {
    asm volatile("stmatrix.sync.aligned.m8n8.x2.trans.shared.b16 [%0], {%1,%2};" :: "r"(a), "r"(r0), "r"(r1) : "memory");
}
__device__ __forceinline__ uint32_t movm(uint32_t a) {
    uint32_t d; asm volatile("movmatrix.sync.aligned.m8n8.trans.b16 %0, %1;" : "=r"(d) : "r"(a)); return d;
}
__device__ __forceinline__ void mma16(float* c, uint32_t a0, uint32_t a1, uint32_t a2, uint32_t a3, uint32_t b0, uint32_t b1) {
    asm volatile("mma.sync.aligned.m16n8k16.row.col.f32.bf16.bf16.f32 {%0,%1,%2,%3}, {%4,%5,%6,%7}, {%8,%9}, {%0,%1,%2,%3};"
                 : "+f"(c[0]), "+f"(c[1]), "+f"(c[2]), "+f"(c[3]) : "r"(a0), "r"(a1), "r"(a2), "r"(a3), "r"(b0), "r"(b1));
}
__device__ __forceinline__ void mma8(float* c, uint32_t a0, uint32_t a1, uint32_t b0) {
    asm volatile("mma.sync.aligned.m16n8k8.row.col.f32.bf16.bf16.f32 {%0,%1,%2,%3}, {%4,%5}, {%6}, {%0,%1,%2,%3};"
                 : "+f"(c[0]), "+f"(c[1]), "+f"(c[2]), "+f"(c[3]) : "r"(a0), "r"(a1), "r"(b0));
}
__device__ __forceinline__ void wg_fence() { asm volatile("wgmma.fence.sync.aligned;" ::: "memory"); }
__device__ __forceinline__ void wg_commit() { asm volatile("wgmma.commit_group.sync.aligned;" ::: "memory"); }
template <int N> __device__ __forceinline__ void wg_wait() { asm volatile("wgmma.wait_group.sync.aligned %0;" :: "n"(N) : "memory"); }
__device__ __forceinline__ uint64_t mkdesc(uint32_t addr, uint32_t lbo, uint32_t sbo, uint32_t swz) {
    return (uint64_t)((addr & 0x3FFFF) >> 4) | ((uint64_t)(lbo >> 4) << 16) | ((uint64_t)(sbo >> 4) << 32) | ((uint64_t)swz << 62);
}
template <int BOFF, int SC>
__device__ __forceinline__ void wgmma_rs16(float* d, uint32_t a0, uint32_t a1, uint32_t a2, uint32_t a3, uint32_t blo) {
    asm volatile("{.reg .pred p; .reg .b32 l; .reg .b64 bd; setp.ne.b32 p, %14, 0; add.u32 l, %12, %13; mov.b64 bd, {l, 40};\n"
                 "wgmma.mma_async.sync.aligned.m64n16k16.f32.bf16.bf16 {%0,%1,%2,%3,%4,%5,%6,%7}, {%8,%9,%10,%11}, bd, p, 1, 1, 0;}"
                 : "+f"(d[0]), "+f"(d[1]), "+f"(d[2]), "+f"(d[3]), "+f"(d[4]), "+f"(d[5]), "+f"(d[6]), "+f"(d[7])
                 : "r"(a0), "r"(a1), "r"(a2), "r"(a3), "r"(blo), "n"(BOFF), "n"(SC));
}
template <int BOFF, int SC>
__device__ __forceinline__ void wgmma_rs32n(float* d, uint32_t a0, uint32_t a1, uint32_t a2, uint32_t a3, uint32_t blo) {
    asm volatile("{.reg .pred p; .reg .b32 l; .reg .b64 bd; setp.ne.b32 p, %22, 0; add.u32 l, %20, %21; mov.b64 bd, {l, 40};\n"
                 "wgmma.mma_async.sync.aligned.m64n32k16.f32.bf16.bf16 "
                 "{%0,%1,%2,%3,%4,%5,%6,%7,%8,%9,%10,%11,%12,%13,%14,%15}, {%16,%17,%18,%19}, bd, p, 1, 1, 0;}"
                 : "+f"(d[0]), "+f"(d[1]), "+f"(d[2]), "+f"(d[3]), "+f"(d[4]), "+f"(d[5]), "+f"(d[6]), "+f"(d[7]),
                   "+f"(d[8]), "+f"(d[9]), "+f"(d[10]), "+f"(d[11]), "+f"(d[12]), "+f"(d[13]), "+f"(d[14]), "+f"(d[15])
                 : "r"(a0), "r"(a1), "r"(a2), "r"(a3), "r"(blo), "n"(BOFF), "n"(SC));
}
template <int BOFF, int SC>
__device__ __forceinline__ void wgmma_rs32(float* d, uint32_t a0, uint32_t a1, uint32_t a2, uint32_t a3, uint32_t blo) {
    asm volatile("{.reg .pred p; .reg .b32 l; .reg .b64 bd; setp.ne.b32 p, %22, 0; add.u32 l, %20, %21; mov.b64 bd, {l, 0x40000040};\n"
                 "wgmma.mma_async.sync.aligned.m64n32k16.f32.bf16.bf16 "
                 "{%0,%1,%2,%3,%4,%5,%6,%7,%8,%9,%10,%11,%12,%13,%14,%15}, {%16,%17,%18,%19}, bd, p, 1, 1, 0;}"
                 : "+f"(d[0]), "+f"(d[1]), "+f"(d[2]), "+f"(d[3]), "+f"(d[4]), "+f"(d[5]), "+f"(d[6]), "+f"(d[7]),
                   "+f"(d[8]), "+f"(d[9]), "+f"(d[10]), "+f"(d[11]), "+f"(d[12]), "+f"(d[13]), "+f"(d[14]), "+f"(d[15])
                 : "r"(a0), "r"(a1), "r"(a2), "r"(a3), "r"(blo), "n"(BOFF), "n"(SC));
}
template <int AOFF, int BOFF, int SC>
__device__ __forceinline__ void wgmma_ss32(float* d, uint32_t alo, uint32_t blo) {
    asm volatile("{.reg .pred p; .reg .b32 l, m; .reg .b64 ad, bd; setp.ne.b32 p, %20, 0; add.u32 l, %16, %18; add.u32 m, %17, %19;\n"
                 "mov.b64 ad, {l, 0x40000040}; mov.b64 bd, {m, 0x40000040};\n"
                 "wgmma.mma_async.sync.aligned.m64n32k16.f32.bf16.bf16 "
                 "{%0,%1,%2,%3,%4,%5,%6,%7,%8,%9,%10,%11,%12,%13,%14,%15}, ad, bd, p, 1, 1, 1, 0;}"
                 : "+f"(d[0]), "+f"(d[1]), "+f"(d[2]), "+f"(d[3]), "+f"(d[4]), "+f"(d[5]), "+f"(d[6]), "+f"(d[7]),
                   "+f"(d[8]), "+f"(d[9]), "+f"(d[10]), "+f"(d[11]), "+f"(d[12]), "+f"(d[13]), "+f"(d[14]), "+f"(d[15])
                 : "r"(alo), "r"(blo), "n"(AOFF), "n"(BOFF), "n"(SC));
}
template <int AOFF, int BOFF, int SC>
__device__ __forceinline__ void wgmma_ss8(float* d, uint32_t alo, uint32_t blo) {
    asm volatile("{.reg .pred p; .reg .b32 l, m; .reg .b64 ad, bd; setp.ne.b32 p, %8, 0; add.u32 l, %4, %6; add.u32 m, %5, %7;\n"
                 "mov.b64 ad, {l, 0x40000040}; mov.b64 bd, {m, 0x8};\n"
                 "wgmma.mma_async.sync.aligned.m64n8k16.f32.bf16.bf16 {%0,%1,%2,%3}, ad, bd, p, 1, 1, 1, 1;}"
                 : "+f"(d[0]), "+f"(d[1]), "+f"(d[2]), "+f"(d[3]) : "r"(alo), "r"(blo), "n"(AOFF), "n"(BOFF), "n"(SC));
}
template <int OFF, int SC>
__device__ __forceinline__ void wgmma_ss40(float* d, uint32_t alo, uint32_t blo) {
    asm volatile("{.reg .pred p; .reg .b32 l, m; .reg .b64 ad, bd; setp.ne.b32 p, %23, 0; add.u32 l, %20, %22; add.u32 m, %21, %22;\n"
                 "mov.b64 ad, {l, 0x40000020}; mov.b64 bd, {m, 0x40000040};\n"
                 "wgmma.mma_async.sync.aligned.m64n40k16.f32.bf16.bf16 "
                 "{%0,%1,%2,%3,%4,%5,%6,%7,%8,%9,%10,%11,%12,%13,%14,%15,%16,%17,%18,%19}, ad, bd, p, 1, 1, 0, 0;}"
                 : "+f"(d[0]), "+f"(d[1]), "+f"(d[2]), "+f"(d[3]), "+f"(d[4]), "+f"(d[5]), "+f"(d[6]), "+f"(d[7]),
                   "+f"(d[8]), "+f"(d[9]), "+f"(d[10]), "+f"(d[11]), "+f"(d[12]), "+f"(d[13]), "+f"(d[14]), "+f"(d[15]),
                   "+f"(d[16]), "+f"(d[17]), "+f"(d[18]), "+f"(d[19])
                 : "r"(alo), "r"(blo), "n"(OFF), "n"(SC));
}
template <int I> using IC = std::integral_constant<int, I>;
template <int I, int N, class F> __device__ __forceinline__ void static_for(F&& f) {
    if constexpr (I < N) { f(std::integral_constant<int, I>{}); static_for<I + 1, N>(f); }
}
__device__ __forceinline__ uint32_t mapa(uint32_t a, uint32_t rank) {
    uint32_t r; asm("mapa.shared::cluster.u32 %0, %1, %2;" : "=r"(r) : "r"(a), "r"(rank)); return r;
}
__device__ __forceinline__ void st_async2(uint32_t a, uint32_t x, uint32_t y, uint32_t bar) {
    asm volatile("st.async.weak.shared::cluster.mbarrier::complete_tx::bytes.v2.b32 [%0], {%1,%2}, [%3];"
                 :: "r"(a), "r"(x), "r"(y), "r"(bar) : "memory");
}
__device__ __forceinline__ void st_async1(uint32_t a, uint32_t x, uint32_t bar) {
    asm volatile("st.async.weak.shared::cluster.mbarrier::complete_tx::bytes.b32 [%0], %1, [%2];" :: "r"(a), "r"(x), "r"(bar) : "memory");
}
__device__ __forceinline__ void st_async4(uint32_t a, uint32_t x, uint32_t y, uint32_t z, uint32_t w, uint32_t bar) {
    asm volatile("st.async.weak.shared::cluster.mbarrier::complete_tx::bytes.v4.b32 [%0], {%1,%2,%3,%4}, [%5];"
                 :: "r"(a), "r"(x), "r"(y), "r"(z), "r"(w), "r"(bar) : "memory");
}
__device__ __forceinline__ void sts2(uint32_t a, uint32_t x, uint32_t y) {
    asm volatile("st.shared.v2.b32 [%0], {%1,%2};" :: "r"(a), "r"(x), "r"(y) : "memory");
}
__device__ __forceinline__ void sts4(uint32_t a, uint4 v) {
    asm volatile("st.shared.v4.b32 [%0], {%1,%2,%3,%4};" :: "r"(a), "r"(v.x), "r"(v.y), "r"(v.z), "r"(v.w) : "memory");
}
__device__ __forceinline__ void sts1(uint32_t a, uint32_t x) { asm volatile("st.shared.b32 [%0], %1;" :: "r"(a), "r"(x) : "memory"); }
__device__ __forceinline__ float2 lds2f(uint32_t a) {
    float2 v; asm volatile("ld.shared.v2.f32 {%0,%1}, [%2];" : "=f"(v.x), "=f"(v.y) : "r"(a) : "memory"); return v;
}
__device__ __forceinline__ uint4 lds4(uint32_t a) {
    uint4 v; asm volatile("ld.shared.v4.b32 {%0,%1,%2,%3}, [%4];" : "=r"(v.x), "=r"(v.y), "=r"(v.z), "=r"(v.w) : "r"(a) : "memory"); return v;
}
__device__ __forceinline__ uint32_t lds1(uint32_t a) {
    uint32_t v; asm volatile("ld.shared.b32 %0, [%1];" : "=r"(v) : "r"(a) : "memory"); return v;
}
__device__ __forceinline__ void stg1(void* p, uint32_t x) { asm volatile("st.global.b32 [%0], %1;" :: "l"(p), "r"(x) : "memory"); }
__device__ __forceinline__ uint32_t ld_acquire(const uint32_t* p) {
    uint32_t v; asm volatile("ld.acquire.gpu.global.u32 %0, [%1];" : "=r"(v) : "l"(p) : "memory"); return v;
}
__device__ __forceinline__ uint32_t ld_relaxed(const void* p) {
    uint32_t v; asm volatile("ld.relaxed.gpu.global.u32 %0, [%1];" : "=r"(v) : "l"(p) : "memory"); return v;
}
__device__ __forceinline__ uint32_t ld_epoch() {
    uint32_t v; asm volatile("ld.relaxed.gpu.global.u32 %0, [%1];" : "=r"(v) : "l"(&g_epoch) : "memory"); return v + 1;
}
__device__ __forceinline__ void st_release(uint32_t* p, uint32_t v) { asm volatile("st.release.gpu.global.u32 [%0], %1;" :: "l"(p), "r"(v) : "memory"); }
__device__ __forceinline__ void st_pkt8(const void* p, uint32_t x, uint32_t y) {
    asm volatile("{.reg .b64 v; mov.b64 v, {%1,%2}; st.relaxed.gpu.global.b64 [%0], v;}" :: "l"(p), "r"(x), "r"(y) : "memory");
}
__device__ __forceinline__ void st_pkt4(const void* p, uint32_t x) {
    asm volatile("st.relaxed.gpu.global.b32 [%0], %1;" :: "l"(p), "r"(x) : "memory");
}
__device__ __forceinline__ uint4 ld_pkt(const void* p) {
    uint4 r;
    asm volatile("{.reg .b64 lo, hi; .reg .b128 v; ld.relaxed.gpu.global.b128 v, [%4]; mov.b128 {lo, hi}, v;\n"
                 "mov.b64 {%0,%1}, lo; mov.b64 {%2,%3}, hi;}"
                 : "=r"(r.x), "=r"(r.y), "=r"(r.z), "=r"(r.w) : "l"(p) : "memory");
    return r;
}

template <int OFF> __device__ __forceinline__ void ld_pkt_stale(uint4& r, const void* p, uint32_t tag) {
    asm volatile("{.reg .pred p; .reg .b32 t; .reg .b64 lo, hi; .reg .b128 v; lop3.b32 t, %0, %5, 1, 0x28; setp.ne.u32 p, t, 0;\n"
                 "mov.b64 lo, {%0,%1}; mov.b64 hi, {%2,%3}; mov.b128 v, {lo, hi}; @p ld.relaxed.gpu.global.b128 v, [%4 + %6];\n"
                 "mov.b128 {lo, hi}, v; mov.b64 {%0,%1}, lo; mov.b64 {%2,%3}, hi;}"
                 : "+r"(r.x), "+r"(r.y), "+r"(r.z), "+r"(r.w) : "l"(p), "r"(tag), "n"(OFF) : "memory");
}

constexpr int NX = 7;
constexpr uint32_t OFF_WV = 0, OFF_WO = 81920, OFF_XR = OFF_WO + 86016, OFF_QA = OFF_XR + NX * 4096, OFF_SP = OFF_QA + 5120, OFF_RED = OFF_SP,
                   OFF_BAR = OFF_SP + 2560, OFF_KA = OFF_QA + 8192, OFF_MEMT = OFF_KA + 5120, OFF_SM = OFF_MEMT + 10240, OFF_PM = OFF_SM + 1280,
                   OFF_SX = OFF_PM + 768, OFF_R1 = OFF_SX + 5120, OFF_OX = OFF_R1, OFF_DBG = OFF_R1 + 4096, CHAIN_SMEM = OFF_DBG + 1024,
                   OFF_OXL = OFF_XR, OFF_OXG = OFF_XR + 4096, OFF_R1L = OFF_XR + 20480, OFF_TRED = OFF_WV + 32768;
__host__ __device__ constexpr uint32_t xblk(int kb) { return kb < 3 ? OFF_MEMT - OFF_XR + kb * 4096 : (kb - 3) * 4096; }
constexpr uint32_t MB_S = OFF_BAR, MB_SX = OFF_BAR + 8, MB_O = OFF_BAR + 16, MB_WO = OFF_BAR + 24, MB_XA = OFF_BAR + 32, MB_XB = OFF_BAR + 40,
                   MB_M = OFF_BAR + 48, MB_EM = OFF_BAR + 88, MB_EA = OFF_BAR + 96, OFF_EP = OFF_BAR + 112,
                   MB_F = OFF_BAR + 128, MB_E = OFF_BAR + 168, OFF_ROLE = OFF_BAR + 224, OFF_T = OFF_BAR + 232, OFF_SPO = OFF_BAR + 236, MB_M2 = OFF_BAR + 240;
constexpr int BAR_QM = 0, BAR_PUB = 1, BAR_QK = 2, BAR_P = 3, BAR_WO = 4, BAR_S = 5, BAR_O2 = 6, BAR_O = 7, BAR_R = 8, BAR_PM = 9, BAR_G = 10,
              BAR_X = 15, BAR_R1 = 15, BAR_MEM = 11;
constexpr float SCL_B = 0.07216878364870322f * 1.4426950408889634f;
#define SW 2
#define NPROBE 3
#define G1 1088
#define G2 1600
#define F1 0
#define F2 0
#define BJ 4
#define NVP 6
#define NVE 6
#define NPF 11
#define NPE 0
#define NPM 6
#define PFD 1
#define XBD 0
#define PFV 1
#define PFX 1
#define PROG 0x5111010101010100ull
#define LEAD 2
#define FEN 0
#define NV0 3
#define HV 1
#define REL 2
#define EB 0
#define NOB 4
#define PW0 7
#define PW1 4
#define NVC 4
#define PWIN 2
#define NCP 1

static_assert(NVC == 4, "first block of v");
__device__ __forceinline__ uint32_t clk32() { uint32_t c; asm volatile("mov.u32 %0, %%clock;" : "=r"(c)); return c; }
__device__ __forceinline__ void spin(uint32_t n) { const uint32_t t = clk32(); while (clk32() - t < n) { } }
__device__ __forceinline__ uint32_t gtime() { uint32_t c; asm volatile("mov.u32 %0, %%globaltimer_lo;" : "=r"(c)); return c; }
__device__ __forceinline__ void ggate(uint32_t t) { while ((int)(gtime() - t) < 0) { } }
__device__ __forceinline__ uint32_t laneid() { uint32_t c; asm volatile("mov.u32 %0, %%laneid;" : "=r"(c)); return c; }
template <int K> __device__ __forceinline__ uint32_t opq0(uint32_t s) { uint32_t c; asm volatile("shr.u32 %0, %1, %2;" : "=r"(c) : "r"(s), "n"(K)); return c; }
__device__ __forceinline__ uint32_t keep(uint32_t x) { asm volatile("" : "+r"(x)); return x; }
template <class T> __device__ __forceinline__ T* keepp(T* p) { asm volatile("" : "+l"(p)); return p; }
__device__ __forceinline__ void sched() { asm volatile("bar.warp.sync 0xffffffff;" ::: "memory"); }
__device__ __forceinline__ void blk(int s) { asm volatile("{.reg .pred p; setp.gt.s32 p, %0, 1000; @p exit;}" :: "r"(s) : "memory"); }
__device__ __forceinline__ uint32_t selu(bool c, uint32_t a, uint32_t b) {
    uint32_t r; asm("{.reg .pred p; setp.ne.u32 p, %1, 0; selp.b32 %0, %2, %3, p;}" : "=r"(r) : "r"((uint32_t)c), "r"(a), "r"(b)); return r;
}
__device__ __forceinline__ float bf_lo(uint32_t w) { return __uint_as_float(w << 16); }
__device__ __forceinline__ float bf_hi(uint32_t w) { return __uint_as_float(w & 0xffff0000u); }
__device__ __forceinline__ uint32_t badd2(uint32_t a, uint32_t b) { uint32_t r; asm("add.rn.bf16x2 %0, %1, %2;" : "=r"(r) : "r"(a), "r"(b)); return r; }
__device__ __forceinline__ uint32_t tagx(uint32_t a, uint32_t b, uint32_t t) { uint32_t r; asm("lop3.b32 %0, %1, %2, %3, 0x7e;" : "=r"(r) : "r"(a), "r"(t), "r"(b)); return r; }
__device__ __forceinline__ uint32_t tagv(uint32_t a, uint32_t b, uint32_t t) { uint32_t r; asm volatile("lop3.b32 %0, %1, %2, %3, 0x7e;" : "=r"(r) : "r"(a), "r"(t), "r"(b)); return r; }
__device__ __forceinline__ uint32_t or3(uint32_t a, uint32_t b, uint32_t c) { uint32_t r; asm("lop3.b32 %0, %1, %2, %3, 0xfe;" : "=r"(r) : "r"(a), "r"(b), "r"(c)); return r; }
__device__ __forceinline__ bool any_bit0(uint32_t a, uint32_t b) {
    uint32_t r;
    asm volatile("{.reg .pred p; .reg .b32 t; lop3.b32 t, %1, 1, %2, 0xc8; setp.ne.u32 p, t, 0; vote.sync.any.pred p, p, 0xffffffff; selp.u32 %0, 1, 0, p;}"
                 : "=r"(r) : "r"(a), "r"(b));
    return r;
}
__device__ __forceinline__ void arrive_e(uint32_t bar) {
    asm volatile("{.reg .pred p; elect.sync _|p, 0xffffffff; @p mbarrier.arrive.shared::cta.b64 _, [%0];}" :: "r"(bar) : "memory");
}
__device__ __forceinline__ void expect_e(uint32_t bar, uint32_t bytes) {
    asm volatile("{.reg .pred p; elect.sync _|p, 0xffffffff; @p mbarrier.arrive.expect_tx.shared::cta.b64 _, [%0], %1;}" :: "r"(bar), "r"(bytes) : "memory");
}
__device__ __forceinline__ void tma2d_e(uint32_t dst, const CUtensorMap* tm, int c0, int c1, uint32_t bar) {
    asm volatile("{.reg .pred p; elect.sync _|p, 0xffffffff;\n"
                 "@p cp.async.bulk.tensor.2d.shared::cluster.global.mbarrier::complete_tx::bytes [%0], [%1, {%3, %4}], [%2];}"
                 :: "r"(dst), "l"(tm), "r"(bar), "r"(c0), "r"(c1) : "memory");
}
__device__ __forceinline__ void ldsm4_if(bool c, uint32_t a, uint32_t& r0, uint32_t& r1, uint32_t& r2, uint32_t& r3) {
    asm volatile("{.reg .pred p; setp.ne.u32 p, %5, 0; @p ldmatrix.sync.aligned.m8n8.x4.shared.b16 {%0,%1,%2,%3}, [%4];}"
                 : "+r"(r0), "+r"(r1), "+r"(r2), "+r"(r3) : "r"(a), "r"((uint32_t)c) : "memory");
}
__device__ __forceinline__ bool arrive_unless(uint32_t a, uint32_t m, int bar, int n) {
    uint32_t r;
    asm volatile("{.reg .pred p; .reg .b32 t; and.b32 t, %1, %2; setp.ne.u32 p, t, 0; vote.sync.any.pred p, p, 0xffffffff; @!p bar.arrive %3, %4;"
                 " selp.u32 %0, 1, 0, p;}" : "=r"(r) : "r"(a), "r"(m), "r"(bar), "r"(n) : "memory");
    return r;
}
__device__ __forceinline__ bool sync_unless(uint32_t a, uint32_t b, uint32_t m, int bar, int n) {
    uint32_t r;
    asm volatile("{.reg .pred p; .reg .b32 t; lop3.b32 t, %1, %2, %3, 0xa8; setp.ne.u32 p, t, 0; vote.sync.any.pred p, p, 0xffffffff; @!p bar.sync %4, %5;"
                 " selp.u32 %0, 1, 0, p;}" : "=r"(r) : "r"(a), "r"(b), "r"(m), "n"(BAR_R), "n"(128) : "memory");
    return r;
}
__device__ __forceinline__ uint32_t pack2v(float lo, float hi) {
    uint32_t r; asm volatile("cvt.rn.bf16x2.f32 %0, %1, %2;" : "=r"(r) : "f"(hi), "f"(lo)); return r;
}
__device__ __forceinline__ void bulk_ld_e(uint32_t dst, const void* src, uint32_t bytes, uint32_t bar) {
    asm volatile("{.reg .pred p; elect.sync _|p, 0xffffffff;\n"
                 "@p cp.async.bulk.shared::cluster.global.mbarrier::complete_tx::bytes [%0], [%1], %2, [%3];}"
                 :: "r"(dst), "l"(src), "r"(bytes), "r"(bar) : "memory");
}
template <int OFF> __device__ __forceinline__ void ld_pkt8(uint32_t& x, uint32_t& y, const void* p) {
    asm volatile("{.reg .b64 v; ld.relaxed.gpu.global.b64 v, [%2 + %3]; mov.b64 {%0,%1}, v;}" : "=r"(x), "=r"(y) : "l"(p), "n"(OFF) : "memory");
}
__device__ __forceinline__ void tma3d_e(uint32_t dst, const CUtensorMap* tm, int c1, int c2, uint32_t bar) {
    asm volatile("{.reg .pred p; elect.sync _|p, 0xffffffff;\n"
                 "@p cp.async.bulk.tensor.3d.shared::cluster.global.mbarrier::complete_tx::bytes [%0], [%1, {0, %3, %4}], [%2];}"
                 :: "r"(dst), "l"(tm), "r"(bar), "r"(c1), "r"(c2) : "memory");
}

constexpr uint32_t XCH_PART = 0x80000;
__device__ __forceinline__ uint32_t xch_line(uint32_t r) { return r ^ ((1 ^ r >> 1 ^ r >> 4 ^ r >> 5) & 1); }
__host__ __device__ constexpr uint32_t xch_mem(uint32_t cg) { return 0x48000 + (cg & 1) * 0x4000 + (cg >> 1) * 0x100000; }
__host__ __device__ constexpr uint32_t xch_copy(uint32_t k) { return (0x22123000u >> 8 * k & 255) << 12; }
__device__ __forceinline__ uint32_t mem_row(uint32_t c) { return (c & 16) * 16 + (c & 4) * 32 + ((((c >> 1) ^ c) & 4) | (c & 3)) * 16; }

#define BORD 0xcb43a29180ull
__host__ __device__ constexpr int bulk_ord(int h) { return (BORD >> 4 * h) & 15; }
__host__ __device__ constexpr int bulk_pos(int k) {
    int r = -1;
    for (int h = 0; h < 10; h++) {
        const int v = bulk_ord(h);
        if ((k == 0 ? (v & 7) == 2 : k == 3 ? (v & 7) < 3 : (v >> 3) == (k == 2)) && (k >= 3 || r < 0)) r = h;
    }
    return r;
}

__device__ __forceinline__ void set_role(uint32_t sb, uint32_t r) {
    const uint32_t role = xch_line(r);
    sts1(sb + OFF_ROLE, role | (xch_mem((role & 255) / 20) + ((role & 255) % 20) * 128) << 2);
    sts1(sb + OFF_SPO, 0x44000 + xch_copy(1 + (role >> 1 & 1)) + (role >> 8) * 4096);
}
__device__ __forceinline__ void pick_role(uint32_t sb, bool second, const char* pp) {
    uint32_t* const g_near = reinterpret_cast<uint32_t*>(g_near4);
    const uint32_t ln = laneid(), ep = lds1(sb + OFF_EP);
    if (!second) {
        if (ln == 0) {
            uint32_t t0 = ~0u, t1 = ~0u;
#pragma unroll 1
            for (int i = 0; i < 2 * NPROBE; i++) {
                const uint32_t c0 = clk32();
                uint32_t c1 = c0 - 1;
                asm volatile("{.reg .pred p; .reg .b32 x; atom.relaxed.gpu.global.exch.b32 x, [%1], %2; setp.le.u32 p, x, %2; @p mov.u32 %0, %%clock;}"
                             : "+r"(c1) : "l"(pp + (i & 1) * 4096), "r"(i) : "memory");
                if (i & 1) t1 = min(t1, c1 - c0); else t0 = min(t0, c1 - c0);
            }
            asm volatile("st.relaxed.gpu.global.v4.b32 [%0], {%1,%1,%1,%1}; st.relaxed.gpu.global.v4.b32 [%0 + 16], {%1,%1,%1,%1};"
                         :: "l"(g_near + blockIdx.x * 8), "r"(ep * 2 + (t1 < t0)) : "memory");
        }
        __syncwarp();
    } else {
        uint32_t a0, a1, a2;
#pragma unroll 1
        for (int c = 0; c < SPIN_LIM; c++) {
            a0 = ld_relaxed(g_near + ln * 24); a1 = ld_relaxed(g_near + ln * 24 + 8); a2 = ld_relaxed(g_near + ln * 24 + 16);
            if (__all_sync(0xffffffffu, ((a0 ^ ep * 2) | (a1 ^ ep * 2) | (a2 ^ ep * 2)) < 2)) break;
            __nanosleep(100);
        }
        const uint32_t bm = __ballot_sync(0xffffffffu, (a0 & 1) + (a1 & 1) + (a2 & 1) >= 2), cl = blockIdx.x / 3;
        const uint32_t side = bm >> cl & 1;
        const int n1 = 3 * __popc(bm), r1 = 3 * __popc(bm & ((1u << cl) - 1));
        const int rk = side ? r1 + blockIdx.x % 3 : blockIdx.x - r1, no = side ? 96 - n1 : n1;
        const uint32_t next = side << 8 | (rk < 40 ? 2 * rk + side : min(2 * (no + rk - 40) + (side ^ 1), 95));
        set_role(sb, next);
    }
}

__host__ __device__ constexpr int out_ord(int n) {
    return n < 8 ? n : n < 8 + LEAD ? 2 * (n - 4) : n >= 24 - LEAD ? 2 * (n - 12) + 1 : (n - LEAD) & 1 ? n - LEAD : n + LEAD;
}
__device__ __forceinline__ void share_o(uint32_t sb, uint32_t rank, uint32_t src, uint32_t t) {
#pragma unroll
    for (uint32_t p = 1; p < 3; p++) {
        const uint32_t pb = mapa(sb, (rank + p) % 3);
        asm volatile("{.reg .pred p; elect.sync _|p, 0xffffffff;\n"
                     "@p cp.async.bulk.shared::cluster.shared::cta.mbarrier::complete_tx::bytes [%0], [%1], 4096, [%2];}"
                     :: "r"(pb + OFF_OXG + t * 8192 + (2 - p) * 4096), "r"(sb + src), "r"(pb + MB_F + 8 * t) : "memory");
    }
}

#define LANE_REGS const uint32_t l16 = __shfl_sync(0xffffffffu, sb + (tid & 31) * 16, tid & 31); const int lane = (l16 - sb) >> 4

__global__ void __cluster_dims__(3, 1, 1) __launch_bounds__(384, 1)
chain_kernel(const __grid_constant__ CUtensorMap tmXA, const __grid_constant__ CUtensorMap tmXB, const __grid_constant__ CUtensorMap tmWq, const __grid_constant__ CUtensorMap tmWk,
             const __grid_constant__ CUtensorMap tmWv, const __grid_constant__ CUtensorMap tmWo,
             const __grid_constant__ CUtensorMap tmOx, const bf16* __restrict__ mem0, const bf16* xb,
             const char* win,
             bf16* out)
{
    extern __shared__ __align__(1024) uint8_t smem[];
    const uint32_t sb = smem_u32(smem);
    const int tid = threadIdx.x;
    const int warp = __shfl_sync(0xffffffffu, tid >> 5, 0);
    uint32_t rank; asm("mov.u32 %0, %%cluster_ctarank;" : "=r"(rank));
    const int head = blockIdx.x / 3;
    const char* pp = win + 0x44000 + (blockIdx.x & 63) * 64 + (blockIdx.x >> 6) * 0x100000;
    if (tid >= 32 && tid < 48) st_pkt4(pp + (tid & 8) * 512 + (tid & 7) * 4, 0);
    const uint32_t ep0 = ld_relaxed(&g_epoch);
    if (tid >= 160 && tid < 240) asm volatile("prefetch.global.L2 [%0];" :: "l"(mem0 + (tid - 160) * 64));

    if (tid == 256) {
        mbar_init(sb + MB_S, 5); mbar_init(sb + MB_SX, 1); mbar_init(sb + MB_O, 1); mbar_init(sb + MB_WO, 1);
        for (int i = 0; i < 4; i++) { mbar_init(sb + MB_M + 8 * i, 1); mbar_init(sb + MB_M2 + 8 * i, 1); }
        mbar_init(sb + MB_XA, 2); mbar_init(sb + MB_XB, 1); mbar_init(sb + MB_EM, 4); mbar_init(sb + MB_EA, 8);
        for (int i = 0; i < 5; i++) { mbar_init(sb + MB_F + 8 * i, 1); mbar_init(sb + MB_E + 8 * i, 8); }
        set_role(sb, blockIdx.x);
        asm volatile("fence.mbarrier_init.release.cluster;" ::: "memory");
        asm volatile("fence.proxy.async.shared::cta;" ::: "memory");
        for (int i = 0; i < PWIN; i++) {
            mbar_expect(sb + MB_F + 8 * i, 32768);
            tma2d(sb + OFF_WV + i * 16384, &tmWq, head * DH + rank * 64, i * 128, sb + MB_F + 8 * i);
            tma2d(sb + OFF_WO + i * 16384, &tmWk, head * DH + rank * 64, i * 128, sb + MB_F + 8 * i);
        }
        mbar_expect(sb + MB_XA, NX * 4096); mbar_expect(sb + MB_XA, 8192); mbar_expect(sb + MB_XB, 4096);
        asm volatile("cp.async.bulk.tensor.3d.shared::cluster.global.mbarrier::complete_tx::bytes [%0], [%1, {0, 0, 3}], [%2];"
                     :: "r"(sb + OFF_XR), "l"(&tmXA), "r"(sb + MB_XA) : "memory");
        for (int i = 0; i < 3; i++)
            asm volatile("cp.async.bulk.tensor.3d.shared::cluster.global.mbarrier::complete_tx::bytes [%0], [%1, {0, 0, %3}], [%2];"
                         :: "r"(sb + OFF_MEMT + i * 4096), "l"(&tmXB), "r"(sb + (i < 2 ? MB_XA : MB_XB)), "r"(i) : "memory");
        mbar_expect(sb + MB_WO, rank == 2 ? 73728 : 86016);
    }
    asm volatile("griddepcontrol.launch_dependents;" ::: "memory");
    __syncthreads();
    asm volatile("barrier.cluster.arrive.release.aligned;" ::: "memory");

    if (warp < 8) {
        asm volatile("setmaxnreg.inc.sync.aligned.u32 224;");
        LANE_REGS;
        const int w4 = warp & 3;
        const uint32_t st0 = __shfl_sync(0xffffffffu, sb + (warp >> 2) * 8192 + ((lane & 7) + ((lane >> 4) << 3)) * 128 +
                                                      (((2 * w4 + ((lane >> 3) & 1)) ^ (lane & 7)) << 4), lane);
        const uint32_t st_addr = st0 + OFF_QA;
        const uint32_t xr_lo = (((sb + OFF_XR) & 0x3FFFF) >> 4) | (1u << 16);
        const uint32_t p1 = mapa(sb, (rank + 1) % 3), p2 = mapa(sb, (rank + 2) % 3), p1s = p1 - sb + OFF_SP, p2s = p2 - sb + OFF_SP + 1280;
        const uint32_t box = rank * 7 + warp;
        const bool act = warp < 7 && box < 20;
        const uint32_t gp = XCH_PART + box * 0x4000 + head * 128;
        const int wg = __reduce_max_sync(0xffffffffu, (unsigned)tid >> 7);
        const uint32_t vo = __reduce_max_sync(0xffffffffu, ((unsigned)tid >> 7) * 32768);
        const uint32_t mo = __reduce_max_sync(0xffffffffu, ((unsigned)tid >> 7) * 5120);
        const uint32_t xa_lo = xr_lo + wg * 5 * 256, xb_lo = xr_lo + xblk(0) / 16 + wg * (2 * 256 - xblk(0) / 16);
        uint32_t wa[80], wb[80];
        {
            const uint32_t src = st_addr - OFF_QA + wg * (40960 - 8192);
            if (wg) { arrive_e(sb + MB_E); arrive_e(sb + MB_E + 8); } else { arrive_e(sb + MB_E + 24); arrive_e(sb + MB_E + 32); }
#pragma unroll
            for (int k = 0; k < 20; k++) {
                if (k % 4 == 0) mbar_wait(sb + MB_F + ((wg * 20 + k) >> 3) * 8, 0);
                ldsm4t(src + wg * OFF_WO + k * 2048, wa[4 * k], wa[4 * k + 1], wa[4 * k + 2], wa[4 * k + 3]);
                ldsm4t(src + (wg ^ 1) * OFF_WO + k * 2048, wb[4 * k], wb[4 * k + 1], wb[4 * k + 2], wb[4 * k + 3]);
                if (k % 4 == 3 && (k == 19 || (k & 4) >> 2 != wg)) arrive_e(sb + MB_E + ((wg * 20 + k) >> 3) * 8);
            }
        }
        asm volatile("barrier.cluster.wait.acquire.aligned;" ::: "memory");
        mbar_wait(sb + MB_XA, 0);

        for (int s = 0; ; s++) {
            uint32_t lb, b[10][4], v[20][4];
            auto ldv = [&](int n) { ldsm4t(st0 + vo + (OFF_WV + n * 2048), v[n][0], v[n][1], v[n][2], v[n][3]); };
            auto ldb = [&](int j) { ldsm4t(lb + mo + (OFF_MEMT + j * 512), b[j][0], b[j][1], b[j][2], b[j][3]); };
#pragma unroll
            for (int n = 0; n < NV0; n++) ldv(n);
            if (s > 0) bar_sync(BAR_WO, 384);
            {
                float pa[16], acc[16];
#pragma unroll
                for (int i = 0; i < 16; i++) pa[i] = acc[i] = 0.f;
                static_for<0, 10>([&](auto H) {
                    constexpr int h = H.value, kb = bulk_ord(h) & 7, own = bulk_ord(h) >> 3;
                    if constexpr (h == bulk_pos(0)) { if (!wg) mbar_wait(sb + MB_XB, s & 1); }
                    if constexpr (h == PW0 && h == bulk_pos(3) + 1) { if (!wg) { wg_wait<0>(); arrive_e(sb + MB_EM); } }
                    if constexpr (h == PW0 || h == PW1) { if (s >= NVC && (PW0 == PW1 || (h == PW0 ? !wg : wg))) { bar_sync(BAR_PUB, 288); } }
                    if (h == 0 || h == bulk_pos(3) + 1 + (PW0 != bulk_pos(3) + 1) || h == bulk_pos(4) + 2 || FEN) wg_fence();
                    static_for<0, 4>([&](auto K4) {
                        constexpr int k4 = K4.value, r = 16 * kb + 4 * k4;
                        const uint32_t* w = own ? wa : wb;
                        wgmma_rs32<(kb < 3 ? kb : kb - 3) * 256 + k4 * 2, k4 != 0 || h != bulk_pos(1 + own)>(own ? acc : pa, w[r], w[r + 1], w[r + 2], w[r + 3], kb < 3 ? xb_lo : xa_lo);
                    });
                    wg_commit();
                    if constexpr (h == HV) {
#pragma unroll
                        for (int n = NV0; n < NVE; n++) ldv(n);
                    }
                    if constexpr (h != PW0 && h == bulk_pos(3) + 1) { if (!wg) { wg_wait<1>(); arrive_e(sb + MB_EM); } }
                    if constexpr (h == bulk_pos(4) + 1) {
                        const uint32_t st_oth = keep((((st0 ^ opq0<8>(s)) - sb) ^ 8192) + sb) + OFF_QA;
                        wg_wait<1>();
                        stsm4t(st_oth + 1024, pack2(pa[0], pa[1]), pack2(pa[2], pa[3]), pack2(pa[4], pa[5]), pack2(pa[6], pa[7]));
                        stsm4t(st_oth + 3072, pack2(pa[8], pa[9]), pack2(pa[10], pa[11]), pack2(pa[12], pa[13]), pack2(pa[14], pa[15]));
                    }
                });
                if (s <= SW) {
                    if (warp == 1 && s) pick_role(sb, s == SW, pp);
                    if (s == 0) {
#pragma unroll 1
                    for (int i = warp >> 1 & 2; i < (warp >> 1 & 2) + 3; i++) { mbar_wait_long(sb + MB_E + 8 * i, 0); mbar_wait_long(sb + MB_F + 8 * i, 1); }
#pragma unroll
                    for (int n = 0; n < NVE; n++) ldv(n);
                    }
                }
                bar_sync(BAR_QK, 256);
                uint32_t u[8];
                ldsm4t(st_addr + 1024, u[0], u[1], u[2], u[3]);
                ldsm4t(st_addr + 3072, u[4], u[5], u[6], u[7]);
#pragma unroll
                for (int n = NVE; n < NVP; n++) ldv(n);
                lb = keep(sb + mem_row(laneid() + opq0<10>(s)));
                wg_wait<0>();
                arrive_e(sb + MB_EA);
#pragma unroll
                for (int i = 0; i < 8; i++) u[i] = badd2(u[i], pack2(acc[2 * i], acc[2 * i + 1]));
                if (EB) { blk(warp); if (wg) bar_sync(BAR_MEM + 2, 160); else bar_sync(BAR_MEM, 160); ldb(0); ldb(1); blk(warp); }
                stsm4t(st_addr + 1024, u[0], u[1], u[2], u[3]);
                stsm4t(st_addr + 3072, u[4], u[5], u[6], u[7]);
            }
            uint32_t lo = 0, so = 0, a[16], kb[8], k1[8];
            const uint32_t r1 = s == NSEG - 1 ? OFF_R1L : OFF_R1;
            float cv[4] = {0, 0, 0, 0};
            {
                float ca[4] = {0, 0, 0, 0}, cb[4] = {0, 0, 0, 0};
                uint32_t sq = 0, ln = 0, lq = 0, lk = 0;
                if (!EB) { blk(warp); if (wg) bar_sync(BAR_MEM + 2, 160); else bar_sync(BAR_MEM, 160); ldb(0); ldb(1); }
#pragma unroll
                for (int j = 0; j < 10; j++) {
                    if (j == BJ) { if (wg) bar_sync(BAR_MEM + 3, 160); else bar_sync(BAR_MEM + 1, 160); if (BJ == 4) ldb(5); }
                    if (j < 3 || (j >= BJ && j < 8)) ldb(j + 2);
                    if (j == 9) {
                        bar_sync(BAR_R1, 288);
#pragma unroll
                        for (int i = 0; i < 4; i++) { kb[i] = b[7][i]; kb[4 + i] = b[8][i]; }
                        ldsm4_if((uint32_t)(warp - 1) < 4, OFF_KA + lo, kb[0], kb[1], kb[2], kb[3]);
                        ldsm4_if((uint32_t)(warp - 1) < 4, OFF_KA + (lo ^ 64), kb[4], kb[5], kb[6], kb[7]);
                    }
                    blk(warp);
#pragma unroll
                    for (int i = 0; i < 2; i++) {
                        const int n = 2 * j + i;
                        mma16(cb, wb[4 * n], wb[4 * n + 1], wb[4 * n + 2], wb[4 * n + 3], b[j][2 * i], b[j][2 * i + 1]);
                        mma16(ca, wa[4 * n], wa[4 * n + 1], wa[4 * n + 2], wa[4 * n + 3], b[j][2 * i], b[j][2 * i + 1]);
                        mma16(cv, v[n][0], v[n][1], v[n][2], v[n][3], b[j][2 * i], b[j][2 * i + 1]);
                        if (n + NVP < 20) ldv(n + NVP);
                    }
                    if (j == 6) { const uint32_t o = (st0 ^ opq0<9>(s)) - sb; ln = keep((o >> 7 & 7) | ((o ^ o >> 3) >> 1 & 8) | (o >> 6 & 16)); }
                    if (j == 7) lo = keep(sb + (ln & 7) * 128 + (((ln >> 3) ^ (ln & 7)) << 4) + warp * 1024);
                    if (j == 8) {
                        lk = keep(sb + ln * 16);
                        sq = keep((lk & ~256u) + (warp & 3) * 256 + selu((ln >> 4) == warp >> 2, r1 + (warp >> 2) * 1024, OFF_KA - (warp >> 2) * 8192));
                        so = keep(sb + warp * 256 + ((ln * 8) ^ (warp & 3) * 32));
                    }
                    if (j == 8) {
                        lq = keep(sb + r1 + (ln & 8) * 128 + (ln >> 4) * 128 + (ln & 7) * 16);
#pragma unroll
                        for (int i = 0; i < 8; i++) k1[i] = opq0<11>(s);
                    }
                }
                a[0] = pack2(ca[0], ca[1]); a[1] = pack2(ca[2], ca[3]); a[2] = pack2(cb[0], cb[1]); a[3] = pack2(cb[2], cb[3]);
                stsm4t(sq, a[0], a[1], a[2], a[3]);
                sts2(so + r1 + 2048, pack2(cv[0], cv[1]), pack2(cv[2], cv[3]));
                bar_sync(BAR_QM, 256);
#pragma unroll
                for (int i = 0; i < 4; i++) { a[4 + i] = __float_as_uint(ca[i]); a[8 + i] = __float_as_uint(cb[i]); a[12 + i] = b[9][i]; }
                ldsm4_if(warp < 5, lq, a[0], a[1], a[2], a[3]);
                ldsm4_if(warp == 0, lk + OFF_KA, kb[0], kb[1], kb[2], kb[3]);
                ldsm4_if(warp < 5, lq + 256, a[4], a[5], a[6], a[7]);
                ldsm4_if(warp == 0, lk + OFF_QA, k1[0], k1[1], k1[2], k1[3]);
                ldsm4_if(warp < 5, lq + 512, a[8], a[9], a[10], a[11]);
                ldsm4_if(warp == 0, lk + OFF_KA + 512, kb[4], kb[5], kb[6], kb[7]);
                ldsm4_if(warp < 5, lq + 768, a[12], a[13], a[14], a[15]);
                ldsm4_if(warp == 0, lk + OFF_QA + 512, k1[4], k1[5], k1[6], k1[7]);
            }
            if (__builtin_expect(warp < 5, 1)) {
                const uint32_t r1a = keep(p1s + so), r2a = keep(p2s + so), m1 = keep(p1 + MB_S), m2 = keep(p2 + MB_S);
                blk(warp);
#pragma unroll
                for (int i = 0; i < 8; i++) kb[i] = badd2(kb[i], k1[i]);
                float d[4][4];
#pragma unroll
                for (int i = 0; i < 4; i++) {
                    d[i][0] = d[i][1] = d[i][2] = d[i][3] = 0.f;
                    mma16(d[i], a[4 * i], a[4 * i + 1], a[4 * i + 2], a[4 * i + 3], kb[2 * i], kb[2 * i + 1]);
                }
                const uint32_t x = __float_as_uint((((d[0][0] + d[0][2]) + (d[1][0] + d[1][2])) + (d[2][0] + d[2][2])) + (d[3][0] + d[3][2]));
                const uint32_t y = __float_as_uint((((d[0][1] + d[0][3]) + (d[1][1] + d[1][3])) + (d[2][1] + d[2][3])) + (d[3][1] + d[3][3]));
                st_async2(r1a, x, y, m1);
                st_async2(r2a, x, y, m2);
                sts2(so + OFF_SM, x, y);
                __syncwarp();
                expect_e(sb + MB_S, 512);
                if (warp == 0) { stsm4(OFF_KA + lo, kb[0], kb[1], kb[2], kb[3]); stsm4(OFF_KA + (lo ^ 64), kb[4], kb[5], kb[6], kb[7]); }
                bar_arrive(BAR_S, 288); bar_arrive(BAR_O2, 256);
            } else {
                if (warp == 7 && s < NSEG - 1) {
                    const uint32_t now = gtime() & ~31u, ln = laneid();
                    if (ln < 4) st_pkt4(win + 0x44000 + xch_copy(1 + (ln & 1)) + (ln >> 1) * 4096 + blockIdx.x * 4, now | ((s - lds1(sb + OFF_EP)) & 3));
                    __syncwarp();
                }
                if (warp == 6 && s < NSEG - 1) {
                    asm volatile("fence.proxy.async.shared::cta;" ::: "memory");
                    expect_e(sb + MB_XA, 8192);
                    tma3d_e(sb + OFF_MEMT, &tmXB, (s + 1) * 32, 0, sb + MB_XA);
                    tma3d_e(sb + OFF_MEMT + 4096, &tmXB, (s + 1) * 32, 1, sb + MB_XA);
                }
                bar_sync(BAR_O2, 256);
            }
            if (s == NSEG - 1) break;
            const uint32_t ln = laneid();
            auto softmax = [&](auto&& more) {
                const uint32_t pb = warp * 32 + (ln & 3) * 8, kt = min(ln >> 2, 4u);
                const uint32_t pw = keep(sb + OFF_PM + pb + selu(ln < 4, 0, pb + 256 + (~ln & 4) * 2 + ((ln + 4) >> 4) * 4));
                const uint32_t sr = keep(sb + OFF_SM + kt * 256 + (pb ^ (kt & 3) * 32));
                mbar_wait(sb + MB_S, s & 1);
                const float2 u = lds2f(sr), t = lds2f(sr + (OFF_SP - OFF_SM)), w = lds2f(sr + (OFF_SP + 1280 - OFF_SM));
                more();
                float x = u.x + t.x + w.x, y = u.y + t.y + w.y;
                int m = __float_as_int(fmaxf(x, y));
                m ^= (m >> 31) & 0x7fffffff;
                m = __reduce_max_sync(0xffffffffu, m);
                m ^= (m >> 31) & 0x7fffffff;
                const float mx = __int_as_float(m) * -SCL_B;
                x = ex2(fmaf(x, SCL_B, mx)); y = ex2(fmaf(y, SCL_B, mx));
                if (ln < 20) sts1(pw, pack2(x, y));
                if (PFD) bar_sync(BAR_PM, 384); else bar_arrive(BAR_PM, 384);
            };
            if (act) {
                const uint32_t wo0 = keep(sb + OFF_WO + warp * 12288 + ((ln & 7) + ((ln >> 4) << 3)) * 64 + ((((ln >> 3) & 1) ^ ((ln >> 1) & 3)) << 4)), wo1 = keep(wo0 ^ 32);
                uint32_t f[24][4];
                auto ld = [&](int n) { ldsm4t((out_ord(n) & 1 ? wo1 : wo0) + (out_ord(n) >> 1) * 1024, f[n][0], f[n][1], f[n][2], f[n][3]); };
#pragma unroll
                for (int n = 0; n < NPE; n++) ld(n);
                softmax([&]() {
#pragma unroll
                    for (int n = NPE; n < NPM; n++) ld(n);
                });
                if (s == 0) {
                    mbar_wait_long(sb + MB_WO, 0);
#pragma unroll
                    for (int n = 0; n < NPM; n++) ld(n);
                }
#pragma unroll
                for (int n = NPM; n < NPF; n++) ld(n);
                const uint32_t l8 = keep(sb + ln * 8);
                const uint32_t tag = (__shfl_sync(0xffffffffu, lds1(sb + OFF_EP), 0) ^ s) & 1;
                const char* dst = nullptr;
                blk(warp);
                bar_sync(BAR_O, 384);
                float2 bb[12];
                auto ldo = [&](int i) { bb[i] = lds2f(l8 + OFF_R1 + (i + 8) % 12 * 256); };
                float e[2][4] = {{0, 0, 0, 0}, {0, 0, 0, 0}};
                int nl = NPF, nb = 0;
#pragma unroll
                for (int n = 0; n < 24; n++) {
                    const int k = out_ord(n) >> 1, t = out_ord(n) & 1;
                    if (n == 8) { bar_sync(BAR_O2, 256); }
                    if (n == 0 || n == 8) { for (int i = 0; i < NOB; i++) ldo(nb++); blk(warp); }
                    mma16(e[t], f[n][0], f[n][1], f[n][2], f[n][3], __float_as_uint(bb[k].x), __float_as_uint(bb[k].y));
                    if (t && nb < (n < 8 ? 4 : 12)) ldo(nb++);
                    if (n > 1 && nl < 24) ld(nl++);
                    if (n == 17) { const uint32_t o = keep(l8); dst = keepp(win + (gp + ((o & 128) << 5) + (o & 127))); }
                    if (n == 23 || (LEAD && n == 24 - LEAD)) {
                        if (n < 23 || !LEAD) st_pkt8(dst, (pack2(e[0][0], e[0][1]) & ~1u) | tag, pack2(e[0][2], e[0][3]));
                        if (n == 23) st_pkt8(dst + 0x2000, (pack2(e[1][0], e[1][1]) & ~1u) | tag, pack2(e[1][2], e[1][3]));
                    }
                    if (t || out_ord(n + 1) % 2 == 0) blk(warp);
                }
            } else {
                softmax([]() { });
                if (warp != 7) { bar_arrive(BAR_O, 384); bar_arrive(BAR_O2, 256); }
                else {
                    const uint32_t now = (gtime() & ~31u) | ((s - lds1(sb + OFF_EP)) & 3);
                    const char* sp = win + (lds1(sb + OFF_SPO) + min(ln, 23u) * 16);
                    expect_e(sb + MB_XB, 4096);
                    bar_sync(BAR_O, 384);
                    asm volatile("fence.proxy.async.shared::cta;" ::: "memory");
                    uint4 sv = ld_pkt(sp);
                    tma3d_e(sb + OFF_MEMT + 8192, &tmXB, (s + 1) * 32, 2, sb + MB_XB);
                    mbar_wait(sb + MB_O, s & 1);
                    bar_arrive(BAR_O2, 256);
                    blk(s);
                    int d;
                    for (int c = 0; ; c++) {
                        const int d0 = sv.x - now, d1 = sv.y - now, d2 = sv.z - now, d3 = sv.w - now;
                        d = max(max(d0, d1), max(d2, d3));
                        if (!__any_sync(0xffffffffu, (d0 | d1 | d2 | d3) & 2) || c == 512) break;
                        sv = ld_pkt(sp);
                    }
                    sts1(sb + OFF_T, (now + min(__reduce_max_sync(0xffffffffu, d), 8192)) & ~31u);
                    bar_arrive(BAR_G, 64);
                    mbar_wait(sb + MB_XA, (s + 1) & 1);
                }
            }
        }
        asm volatile("setmaxnreg.dec.sync.aligned.u32 168;");
        uint32_t f[24][4];
        const uint32_t lnt = laneid(), ep = lds1(sb + OFF_EP);
        {
            const uint32_t wo0 = sb + OFF_WO + warp * 12288 + ((lnt & 7) + ((lnt >> 4) << 3)) * 64 + ((((lnt >> 3) & 1) ^ ((lnt >> 1) & 3)) << 4);
#pragma unroll
            for (int n = 0; n < 24; n++) ldsm4t((wo0 ^ (n / 12) * 32) + (n % 12) * 1024, f[n][0], f[n][1], f[n][2], f[n][3]);
        }
        char* tp = reinterpret_cast<char*>(g_tail) + head * 40960 + box * 2048;
        uint32_t ts = sb + OFF_WV + warp * 2048;
        const uint32_t o16 = lnt * 16;
#pragma unroll 1
        for (int t = 0; t < 2; t++) {
            const uint32_t b0 = (((sb + (t ? OFF_OXL : OFF_OX)) & 0x3FFFF) >> 4) | (1u << 16), b1 = (((sb + OFF_OXG + t * 8192) & 0x3FFFF) >> 4) | (1u << 16);
            float acc[2][16];
#pragma unroll
            for (int i = 0; i < 16; i++) acc[0][i] = acc[1][i] = 0.f;
            auto st = [&](int i) {
                const float* a = acc[i];
                sts4(ts + o16 + i * 1024, make_uint4((pack2(a[0], a[1]) & ~1u) | (ep & 1), pack2(a[2], a[3]), pack2(a[4], a[5]), pack2(a[6], a[7])));
                sts4(ts + o16 + i * 1024 + 512, make_uint4((pack2(a[8], a[9]) & ~1u) | (ep & 1), pack2(a[10], a[11]), pack2(a[12], a[13]), pack2(a[14], a[15])));
                asm volatile("fence.proxy.async.shared::cta;" ::: "memory");
                __syncwarp();
                asm volatile("{.reg .pred p; elect.sync _|p, 0xffffffff; @p cp.async.bulk.global.shared::cta.bulk_group [%0], [%1], 1024;}"
                             :: "l"(tp + i * 1024), "r"(ts + i * 1024) : "memory");
            };
            if (t) bar_sync(BAR_WO, 384);
            wg_fence();
            static_for<0, 8>([&](auto N) {
                constexpr int i = N.value >> 2, k = N.value & 3;
                wgmma_rs32<k * 2, k != 0>(acc[i], f[12 * i + k][0], f[12 * i + k][1], f[12 * i + k][2], f[12 * i + k][3], b0);
            });
            wg_commit();
            mbar_wait(sb + MB_F + 8 * t, 0);
            static_for<0, 2>([&](auto I) {
                constexpr int i = I.value;
                wg_fence();
                static_for<4, 12>([&](auto K) {
                    constexpr int k = K.value;
                    wgmma_rs32<(k / 4 - 1) * 256 + (k & 3) * 2, 1>(acc[i], f[12 * i + k][0], f[12 * i + k][1], f[12 * i + k][2], f[12 * i + k][3], b1);
                });
                wg_commit();
            });
            wg_wait<1>();
            if (act) st(0);
            wg_wait<0>();
            if (act) st(1);
            if (t) bar_arrive(BAR_X, 384);
            tp += 32 * 40960; ts += 16384;
        }
        asm volatile("cp.async.bulk.commit_group;" ::: "memory");
        asm volatile("cp.async.bulk.wait_group.read 0;" ::: "memory");
    } else {
        asm volatile("setmaxnreg.dec.sync.aligned.u32 56;");
        const int g = __reduce_max_sync(0xffffffffu, (unsigned)tid >> 5 & 3);
        const uint32_t ep = __reduce_max_sync(0xffffffffu, ep0) + 1;
        sts1(sb + OFF_EP, ep);
#pragma unroll
        for (int i = 0; i < 5; i++) {
            const unsigned short* m = reinterpret_cast<const unsigned short*>(mem0) + g * 160 + (tid & 31) + 32 * i;
            sts4(sb + (tid & 127) * 16 + (i < 4 ? OFF_SX + i * 2048 : OFF_WO + 81920),
                 make_uint4(m[0] | ((uint32_t)m[DM] << 16), m[2 * DM] | ((uint32_t)m[3 * DM] << 16),
                            m[4 * DM] | ((uint32_t)m[5 * DM] << 16), m[6 * DM] | ((uint32_t)m[7 * DM] << 16)));
        }
        asm volatile("barrier.cluster.wait.acquire.aligned;" ::: "memory");
        if (g == 0) {
            const int e0 = head * DH + rank * 64;
            for (int i = PWIN; i < 5; i++) {
                mbar_wait(sb + MB_F + 8 * (i - PWIN), 0);
                expect_e(sb + MB_F + 8 * i, 32768);
                tma2d_e(sb + OFF_WV + i * 16384, &tmWq, e0, i * 128, sb + MB_F + 8 * i);
                tma2d_e(sb + OFF_WO + i * 16384, &tmWk, e0, i * 128, sb + MB_F + 8 * i);
            }
            for (int i = 0; i < 5; i++) {
                mbar_wait(sb + MB_E + 8 * i, 0);
                if (i + 5 - PWIN < 5) mbar_wait(sb + MB_F + 8 * (i + 5 - PWIN), 0);
                expect_e(sb + MB_F + 8 * i, 16384);
                tma2d_e(sb + OFF_WV + i * 16384, &tmWv, e0, i * 128, sb + MB_F + 8 * i);
            }
        }
        uint32_t role = 0, ph = 0, tg = 0;
        uint32_t o16 = __shfl_sync(0xffffffffu, (tid & 31) * 16, tid & 31);
        auto gather = [&](int s) {
            const char* mb = win + (role >> 8 & 1) * 4096 + xch_copy((role >> 1) % NCP);
            mbar_wait(sb + MB_EM, s & 1);
            ggate(tg + G2);
            if (F2) spin(F2);
#pragma unroll
            for (int i = 0; i < 4; i++) { const int c = (i & 1) * 2 + (i >> 1); bulk_ld_e(sb + OFF_MEMT + c * 2560, mb + xch_mem(c), 2560, sb + MB_M + 8 * c); }
            bar_arrive(BAR_G, 64);
        };

        for (int s = 0; ; s++) {
            uint32_t vx[8];
            o16 += opq0<8>(s);
            const uint32_t lz = sb + o16;
            const uint4* vp = keepp(g_vx + (blockIdx.x * 64 + s) * 256 + g * 32 + (o16 >> 4));
            auto load_v = [&]() {
                const uint4 u = ld_pkt(vp), v = ld_pkt(vp + 128);
                vx[0] = u.x; vx[2] = u.y; vx[1] = u.z; vx[3] = u.w; vx[4] = v.x; vx[6] = v.y; vx[5] = v.z; vx[7] = v.w;
            };
            const char* mb = win + (role >> 8 & 1) * 4096 + xch_copy((role >> 1) % NCP);
            auto store_x = [&]() {
                if (g == 3) {
                    bar_sync(BAR_G, 64);
                    if (o16 == 0 && s < NSEG - 1) { tma_st(&tmOx, sb + OFF_OX, blockIdx.x * 64, (s - 1) * 32); asm volatile("cp.async.bulk.commit_group;" ::: "memory"); }
                    __syncwarp();
                }
            };
#pragma unroll
            for (int j = 0; j < 8; j++) vx[j] = 0;
            if (s > NVC) load_v();
            if (s >= NVC) store_x();
            if (s < NVC) {
                const uint32_t wv_lo = (((sb + OFF_WV) & 0x3FFFF) >> 4) | (64u << 16), xr_lo = (((sb + OFF_XR) & 0x3FFFF) >> 4) | (1u << 16);
                float acc[16];
#pragma unroll
                for (int i = 0; i < 16; i++) acc[i] = 0.f;
                mbar_wait(sb + MB_XA, s & 1);
                mbar_wait(sb + MB_XB, s & 1);
                static_for<0, 10>([&](auto KB) {
                    constexpr uint32_t kb = KB.value;
                    if (kb == 4) {
                        wg_wait<1>();
                        bar_sync(BAR_P, 128);
                        if (s > 0) { if (g == 1) gather(s); store_x(); }
                        else {
                            const uint32_t ln = laneid();
                            mbar_wait_long(sb + MB_EM, 0);
#pragma unroll
                            for (int i = 0; i < 5; i++)
                                sts4(sb + mem_row(ln) + OFF_MEMT + g * 2560 + 512 * i, lds4(sb + g * 512 + ln * 16 + (i < 4 ? OFF_SX + i * 2048 : OFF_WO + 81920)));
                            asm volatile("fence.proxy.async.shared::cta;" ::: "memory");
                            bar_sync(BAR_P, 128);
                            arrive_e(sb + MB_M + 8 * g);
                        }
                    }
                    if (!(kb & 1) && s == 0) {
                        mbar_wait_long(sb + MB_E + 4 * kb, 0);
                        mbar_wait_long(sb + MB_F + 4 * kb, 1);
                        if (g == 0) {
#pragma unroll 1
                            for (uint32_t n = 2 * kb; n < (kb == 8 ? (rank == 2 ? 18 : 21) : 2 * kb + 4); n++)
                                tma2d_e(sb + OFF_WO + n * 4096, &tmWo, (rank * 7 + n / 3) * 32, head * DH + (rank + n) % 3 * 64, sb + MB_WO);
                        }
                    }
                    wg_fence();
                    static_for<0, 4>([&](auto K4) { wgmma_ss32<(kb * 4 + K4.value) * 128, xblk(kb) / 16 + K4.value * 2, (kb | K4.value) != 0>(acc, wv_lo, xr_lo); });
                    wg_commit();
                });
                wg_wait<0>();
#pragma unroll
                for (int j = 0; j < 8; j++) vx[j] = pack2(acc[2 * j], acc[2 * j + 1]);
                bar_sync(BAR_P, 128);
            }
            const uint32_t* fv = g_flagv + blockIdx.x * 64 + (s == NVC ? s : s + 1);
            uint32_t fl = ep;
            if (s == NVC || (g == 0 && (s & 7) == 7 && s < NSEG - 1)) fl = ld_relaxed(fv);
            {
                const uint32_t mt = keep(lz + OFF_MEMT + g * 2560), tag = (s ^ ep ^ 1) & 1, msk = keep(s > 0);
                const int bar = keep(BAR_MEM + g);
                auto stale = [&](uint32_t m) {
                    uint4 q[5];
#pragma unroll
                    for (int i = 0; i < 5; i++) q[i] = lds4(mt + 512 * i);
                    uint32_t bad = 0;
#pragma unroll
                    for (int i = 0; i < 5; i++) bad = or3(bad, tagx(q[i].x, q[i].y, tag), tagx(q[i].z, q[i].w, tag));
                    return arrive_unless(bad, m, bar, 160);
                };
                mbar_wait_long(sb + MB_M + 8 * g, s & 1);
                if (stale(msk)) {
                    for (int cnt = 0; ; cnt++) {
                        asm volatile("fence.proxy.async.shared::cta;" ::: "memory");
                        __syncwarp();
                        expect_e(sb + MB_M2 + 8 * g, 2560);
                        bulk_ld_e(sb + OFF_MEMT + g * 2560, mb + xch_mem(g), 2560, sb + MB_M2 + 8 * g);
                        mbar_wait_long(sb + MB_M2 + 8 * g, ph);
                        ph ^= 1;
                        if (!stale(cnt < WAIT_LIM)) break;
                    }
                }
                if (g == 3) { asm volatile("cp.async.bulk.wait_group.read 0;" ::: "memory"); __syncwarp(); bar_arrive(BAR_R1, 288); }
            }
            if (g == 1 && s < NSEG - 1) {
                mbar_wait(sb + MB_EA, s & 1);
                expect_e(sb + MB_XA, NX * 4096);
                tma3d_e(sb + OFF_XR, &tmXA, (s + 1) * 32, 3, sb + MB_XA);
            }
            if (fl != ep) for (int c = 0; c < SPIN_LIM && ld_acquire(fv) != ep; c++) { }
            if (s == NVC) load_v();
            if (PFV && g == 0 && s >= NVC && s < NSEG - 1) asm volatile("prefetch.global.L2 [%0];" :: "l"(g_vx + (blockIdx.x * 64 + s + 1) * 256 + (o16 >> 1)));
            if (PFX && g == 2 && s < NSEG - 2 && blockIdx.x < 80 && o16 < 64)
                asm volatile("prefetch.global.L2 [%0];" :: "l"(reinterpret_cast<const char*>(xb) + (s + 2) * 40960 + blockIdx.x * 512 + o16 * 8));
            if (s < NSEG - 1) {
                if (g == 0) expect_e(sb + MB_O, 2048);
            } else if (g == 0) {
                expect_e(sb + MB_F, 8192); expect_e(sb + MB_F + 8, 8192);
            }
            if (g == 1) expect_e(sb + MB_SX, 5120);
            auto progress = [&]() {
                if (g == 3 && (PROG >> s & 1)) {
                    if (o16 == 0) {
                        asm volatile("cp.async.bulk.wait_group 0;" ::: "memory");
                        st_pkt4(g_prog + blockIdx.x + (keep(s) >> 8), ep * 128 + s);
                    }
                    __syncwarp();
                }
            };
            progress();
            const uint32_t q1 = keep(mapa(sb, (rank + 1) % 3) - sb), q2 = keep(mapa(sb, (rank + 2) % 3) - sb);
            uint32_t own[5], vm0, vm1;
            {
                const uint32_t qa_lo = (((sb + OFF_QA + 1024) & 0x3FFFF) >> 4) | (1u << 16), ka_lo = (((sb + OFF_KA) & 0x3FFFF) >> 4) | (1u << 16);
                const uint32_t va = keep(sb + ((o16 >> 1) ^ g * 32) + g * 256 + (s == NSEG - 1 ? OFF_R1L : OFF_R1) + 2048);
                float d[20];
#pragma unroll
                for (int j = 0; j < 20; j++) d[j] = 0.f;
                bar_sync(BAR_S, 288);
                const float2 u = lds2f(va), v = lds2f(va + 1024);
                role = __shfl_sync(0xffffffffu, lds1(sb + OFF_ROLE), 0);
                asm volatile("fence.proxy.async.shared::cta;" ::: "memory");
                wg_fence();
                static_for<0, 4>([&](auto K4) { wgmma_ss40<K4.value * 2, K4.value != 0>(d, qa_lo, ka_lo); });
                wg_commit();
                if (s < NSEG - 1) expect_e(sb + MB_M + 8 * g, 2560);
                vm0 = badd2(__float_as_uint(u.x), __float_as_uint(v.x)); vm1 = badd2(__float_as_uint(u.y), __float_as_uint(v.y));
                const uint32_t xo = lz + OFF_SX + g * 640, mo = sb + OFF_SX + g * 640 + 512 + (o16 >> 2);
                const int lim = 8 + 8 * g + (o16 >> 6) - ((o16 >> 3) & 6);
                wg_wait<0>();
#pragma unroll
                for (int j = 0; j < 5; j++) own[j] = pack2(8 * j > lim ? -INFINITY : d[4 * j], 8 * j + 1 > lim ? -INFINITY : d[4 * j + 1]);
                mbar_wait(sb + MB_S, s & 1);
                st_async4(q1 + xo + 2560, own[1], own[2], own[3], own[4], q1 + sb + MB_SX); st_async4(q2 + xo, own[1], own[2], own[3], own[4], q2 + sb + MB_SX);
                st_async1(q1 + mo + 2560, own[0], q1 + sb + MB_SX);                         st_async1(q2 + mo, own[0], q2 + sb + MB_SX);
            }
            if (s < NSEG - 1) {
                const uint32_t pm = keep(sb + OFF_PM + (o16 >> 1)), oo = keep(pm + (OFF_R1 - OFF_PM) + g * 256);
                blk(s);
                bar_sync(BAR_PM, 384);
                const uint4 qq = lds4(lz + OFF_PM + 256);
                const uint32_t p0 = lds1(pm);
                float oa[2][4] = {{0, 0, 0, 0}, {0, 0, 0, 0}}, ob[2][4] = {{0, 0, 0, 0}, {0, 0, 0, 0}}, os[4] = {0, 0, 0, 0};
                mma16(os, qq.x, qq.y, qq.z, qq.w, 0x3f803f80, 0x3f803f80);
                mma16(oa[0], qq.x, qq.y, qq.z, qq.w, vx[0], vx[2]);
                mma16(oa[1], qq.x, qq.y, qq.z, qq.w, vx[1], vx[3]);
                mma16(ob[0], qq.x, qq.y, qq.z, qq.w, vx[4], vx[6]);
                mma8(os, p0, 0, 0x3f803f80);
                mma16(ob[1], qq.x, qq.y, qq.z, qq.w, vx[5], vx[7]);
                mma8(oa[0], p0, 0, vm0);
                mma8(oa[1], p0, 0, vm1);
                const float inv = rcpf(os[0] + os[2]);
                const uint32_t o0 = pack2((oa[0][0] + ob[0][2]) * inv, (oa[0][1] + ob[0][3]) * inv), o1 = pack2((oa[1][0] + ob[1][2]) * inv, (oa[1][1] + ob[1][3]) * inv);
                st_async2(q1 + oo + 1024, o0, o1, q1 + sb + MB_O);
                st_async2(q2 + oo, o0, o1, q2 + sb + MB_O);
                sts2(oo + 2048, o0, o1);
                bar_arrive(BAR_O, 384);
            } else if (g == 1) {
                share_o(sb, rank, OFF_OX, 0);
            }
            {
                float sc[10], mx;
                const uint32_t xo = lz + OFF_SX + g * 640, pa = sb + OFF_SX + g * 640 + (o16 >> 2);
                mbar_wait(sb + MB_SX, s & 1);
                const uint4 u = lds4(xo), v = lds4(xo + 2560);
                const uint32_t um = lds1(pa + 512), vm = lds1(pa + 512 + 2560);
#define SSUM(k, a, b, c) sc[k] = (bf_lo(a) + bf_lo(b)) + bf_lo(c); sc[k + 1] = (bf_hi(a) + bf_hi(b)) + bf_hi(c);
                SSUM(0, own[0], um, vm) SSUM(2, own[1], u.x, v.x) SSUM(4, own[2], u.y, v.y) SSUM(6, own[3], u.z, v.z) SSUM(8, own[4], u.w, v.w)
#undef SSUM
                mx = fmaxf(fmaxf(fmaxf(sc[2], sc[3]), fmaxf(sc[4], sc[5])), fmaxf(fmaxf(fmaxf(sc[6], sc[7]), fmaxf(sc[8], sc[9])), fmaxf(sc[0], sc[1])));
                mx = fmaxf(fmaxf(mx, __shfl_xor_sync(0xffffffffu, mx, 1)), fmaxf(__shfl_xor_sync(0xffffffffu, mx, 2), __shfl_xor_sync(0xffffffffu, mx, 3)));
                mx *= -SCL_B;
                float sum = 0.f;
#pragma unroll
                for (int j = 0; j < 10; j++) { sc[j] = ex2(fmaf(sc[j], SCL_B, mx)); sum += sc[j]; }
                sum = (sum + __shfl_xor_sync(0xffffffffu, sum, 1)) + (__shfl_xor_sync(0xffffffffu, sum, 2) + __shfl_xor_sync(0xffffffffu, sum, 3));
                const float inv = rcpf(sum);
#pragma unroll
                for (int j = 0; j < 5; j++) sts1(pa + j * 128, pack2(sc[2 * j] * inv, sc[2 * j + 1] * inv));
                asm volatile("fence.proxy.async.shared::cta;" ::: "memory");
            }
            float acc[16];
            {
                const uint32_t px_lo = (((sb + OFF_SX) & 0x3FFFF) >> 4) | (8u << 16);
                uint32_t a[12];
                const uint32_t z = opq0<8>(s);
#pragma unroll
                for (int i = 0; i < 12; i++) asm volatile("xor.b32 %0, %1, %2;" : "=r"(a[i]) : "r"(i < 8 ? vx[i & 7] : i == 8 ? vm0 : i == 9 ? vm1 : 0u), "r"(z));
#pragma unroll
                for (int i = 0; i < 16; i++) acc[i] = 0.f;
                if (g == 1 && s < NSEG - 1) { bar_sync(BAR_G, 64); tg = lds1(sb + OFF_T); }
                if (s < NSEG - 1) bar_sync(BAR_WO, 384); else bar_sync(BAR_P, 128);
                wg_fence();
                wgmma_rs32n<0, 0>(acc, a[8], a[9], a[10], a[11], px_lo);
                wgmma_rs32n<8, 1>(acc, a[0], a[1], a[2], a[3], px_lo);
                wgmma_rs32n<24, 1>(acc, a[4], a[5], a[6], a[7], px_lo);
                wg_commit();
            }
            o16 += opq0<9>(s);
            const uint32_t ln = o16 >> 4;
            const uint32_t sa = keep(sb + (s == NSEG - 1 ? OFF_OXL : OFF_OX) + ((ln & 7) + ((ln >> 4) << 3)) * 128 + (((2 * g + ((ln >> 3) & 1)) ^ (ln & 7)) << 4));
            auto store_o = [&]() {
                wg_wait<0>();
                stsm4t(sa, pack2v(acc[0], acc[1]), pack2v(acc[2], acc[3]), pack2v(acc[4], acc[5]), pack2v(acc[6], acc[7]));
                stsm4t(sa + 2048, pack2v(acc[8], acc[9]), pack2v(acc[10], acc[11]), pack2v(acc[12], acc[13]), pack2v(acc[14], acc[15]));
            };
            if ((role & 255) < 80 && s < NSEG - 1) {
                const char* rp = keepp(win + (XCH_PART + (role & 255) * 4096 + g * 1024 + (o16 >> 1)));
                const char* wp = keepp(win + ((role >> 9 << 7) + (((o16 >> 4 ^ role) & 1) * 4 + (o16 >> 7)) * 16 + (o16 >> 3 & 12)));
                const uint32_t tag = (s ^ ep) & 1, rb = keep(sb + (o16 >> 1));
                uint32_t x[4], y[4];
                auto load = [&]() { static_for<0, 4>([&](auto I) { ld_pkt8<I.value * 256>(x[I.value], y[I.value], rp); }); };
                auto sum8 = [&](uint32_t m) {
                    sts4(sb + o16 + OFF_RED + g * 512,
                         make_uint4(__float_as_uint(((bf_lo(x[0]) + bf_lo(x[1])) + bf_lo(x[2])) + bf_lo(x[3])), __float_as_uint(((bf_hi(x[0]) + bf_hi(x[1])) + bf_hi(x[2])) + bf_hi(x[3])),
                                    __float_as_uint(((bf_lo(y[0]) + bf_lo(y[1])) + bf_lo(y[2])) + bf_lo(y[3])), __float_as_uint(((bf_hi(y[0]) + bf_hi(y[1])) + bf_hi(y[2])) + bf_hi(y[3]))));
                    return sync_unless(tagx(x[0], x[1], tag), tagx(x[2], x[3], tag), m, BAR_R, 128);
                };
                auto again = [&]() { for (int cnt = 0; ; cnt++) { load(); if (!sum8(cnt < WAIT_LIM)) break; } };
                if (g == 0) {
                    bar_sync(BAR_R, 128);
                    load();
                    store_o();
                    const bool st = sum8(1);
                    float2 r[8];
#pragma unroll
                    for (int i = 0; i < 8; i++) r[i] = lds2f(rb + OFF_RED + i * 256);
                    if (REL == 1 && s >= NVC - 1) bar_arrive(BAR_PUB, 288);
                    if (st) {
                        again();
#pragma unroll
                        for (int i = 0; i < 8; i++) r[i] = lds2f(rb + OFF_RED + i * 256);
                    }
                    const float k0 = ((r[0].x + r[1].x) + (r[2].x + r[3].x)) + ((r[4].x + r[5].x) + (r[6].x + r[7].x));
                    const float k1 = ((r[0].y + r[1].y) + (r[2].y + r[3].y)) + ((r[4].y + r[5].y) + (r[6].y + r[7].y));
                    const uint32_t kb = __float_as_uint(k0);
                    const uint32_t pk = __byte_perm(kb + ((kb ^ tag << 16) & 0x10000), pack2(0.f, k1), 0x7632);
#pragma unroll
                    for (int i = 0; i < 2 * NCP; i++) st_pkt4(wp + xch_copy(i >> 1) + (i & 1) * 4096, pk);
                    if (REL == 2 && s >= NVC - 1) bar_arrive(BAR_PUB, 288);
                } else {
                    if (g == 1) { ggate(tg + G1); if (F1) spin(F1); }
                    bar_sync(BAR_R, 128);
                    load();
                    store_o();
                    if (sum8(1)) again();
                }
            } else {
                store_o();
                if (s == NSEG - 1) {
                    asm volatile("fence.proxy.async.shared::cta;" ::: "memory");
                    bar_arrive(BAR_WO, 384);
                    bar_sync(BAR_P, 128);
                    if (g == 1) share_o(sb, rank, OFF_OXL, 1);
                    break;
                }
                bar_sync(BAR_R, 128);
                if (g == 0 && s >= NVC - 1) bar_arrive(BAR_PUB, 288);
            }
            if (g == 1 && s >= NVC - 1) gather(s + 1);
            if (g == 3) asm volatile("fence.proxy.async.shared::cta;" ::: "memory");
        }
        uint32_t u, c, sb2;
        asm volatile("mov.u32 %0, %%tid.x; mov.u32 %1, %%ctaid.x; mov.u32 %2, %%dynamic_smem_size;" : "=r"(u), "=r"(c), "=r"(sb2));
        sb2 += sb - CHAIN_SMEM;
        const uint32_t g2 = __shfl_sync(0xffffffffu, (u >> 5) & 3, 0), ln = u & 31;
        asm volatile("setmaxnreg.inc.sync.aligned.u32 96;");
        const uint32_t et = ld_epoch();
        const uint4* rp = g_tail + g2 * 8 * 2560 + c * 32 + ln;
        bf16* op = out + (size_t)((NSEG - 2) * 32 + (c & 1) * 16 + (g2 >> 1) * 8 + (ln >> 2)) * OUTW + DM + (c >> 1) * 16 + (g2 & 1) * 8 + (ln & 3) * 2;
#pragma unroll 1
        for (int t = 0; t < 2; t++) {
            if (t == 0) bar_sync(BAR_X, 384);
            if (c >= 80) continue;
            uint4 q[8];
#pragma unroll
            for (int i = 0; i < 8; i++) q[i] = ld_pkt(rp + 2560 * i);
            for (int cnt = 4 * WAIT_LIM; cnt; cnt--) {
                uint32_t bad = 0;
#pragma unroll
                for (int i = 0; i < 8; i++) bad |= q[i].x ^ et;
                if (!any_bit0(bad, bad)) break;
                static_for<0, 8>([&](auto I) { ld_pkt_stale<I.value * 40960>(q[I.value], rp, et); });
            }
            float r[8] = {0, 0, 0, 0, 0, 0, 0, 0};
#pragma unroll
            for (int i = 0; i < 8; i++) {
                r[0] += bf_lo(q[i].x); r[1] += bf_hi(q[i].x); r[2] += bf_lo(q[i].y); r[3] += bf_hi(q[i].y);
                r[4] += bf_lo(q[i].z); r[5] += bf_hi(q[i].z); r[6] += bf_lo(q[i].w); r[7] += bf_hi(q[i].w);
            }
            const uint32_t ra = sb2 + OFF_TRED + t * 4096 + ln * 8, rb2 = ra + g2 * 1024;
#pragma unroll
            for (int j = 0; j < 4; j++) sts2(ra + j * 1024 + g2 * 256, __float_as_uint(r[2 * j]), __float_as_uint(r[2 * j + 1]));
            bar_sync(BAR_R, 128);
            const float2 x0 = lds2f(rb2), x1 = lds2f(rb2 + 256), x2 = lds2f(rb2 + 512), x3 = lds2f(rb2 + 768);
            stg1(op, movm(pack2((x0.x + x1.x) + (x2.x + x3.x), (x0.y + x1.y) + (x2.y + x3.y))));
            rp += 32 * 2560;
            op += 32 * OUTW;
        }
    }
    asm volatile("barrier.cluster.arrive.release.aligned;" ::: "memory");
    asm volatile("barrier.cluster.wait.acquire.aligned;" ::: "memory");
}

constexpr int NSIDE = 36, SST = 3, MAXJ = 44, NKS = 7;
constexpr uint32_t S_STAGE = 49152, S_STG = SST * S_STAGE, S_RST = S_STG + 65536, S_BAR = S_RST + 12288, SIDE_SMEM = S_BAR + 256;
constexpr uint32_t SB_FULL = S_BAR, SB_EMPTY = S_BAR + 64, SB_STAGED = S_BAR + 32, SB_FREE = S_BAR + 48;
constexpr uint32_t SB_FINE = 128;
enum { JV = 0, JQ = 1, JP = 2, JO = 3, JR = 4, JEND = 5 };
struct SideParams {
    CUtensorMap a[4], b[4], c[3], st[2], sto;
};
struct Job { uint32_t x, y; };
struct JobTable { Job j[NSIDE][MAXJ]; };
static_assert(OFF_OX % 1024 == 0 && OFF_QA % 1024 == 0 && OFF_MEMT % 1024 == 0, "swizzled tiles");
__constant__ const JobTable c_jobs = {{
    {{0x8020,0xa0000},{0x9220,0xa0000},{0x104c0,0xa0000},{0x116c0,0xa0000},{0x201c0,0xa0000},{0x213c0,0xa0000},{0x303c0,0xa0000},{0x31340,0xa0000},{0x50341,0xa0000},{0x408c0,0xa0000},{0x415c0,0xa0000},{0x70341,0xa0000},{0x20043,0x600200},{0x501c2,0xa0000},{0x50043,0x10e0500},{0x60023,0x10e0600},{0x23600a3,0x10d0605},{0x68023,0x10e0700},{0x70023,0x10e0800},{0x68024,0x1000705},{0x78013,0x10e0900},{0x70024,0x1000803},{0x78014,0x1000901},{5,0}},
    {{0x80a0,0xa0000},{0x92a0,0xa0000},{0x10540,0xa0000},{0x11740,0xa0000},{0x20240,0xa0000},{0x21440,0xa0000},{0x30440,0xa0000},{0x313c0,0xa0000},{0x503c1,0xa0000},{0x40940,0xa0000},{0x41640,0xa0000},{0x703c1,0xa0000},{0x200c3,0x600200},{0x50242,0xa0000},{0x500c3,0x10e0500},{0x600a3,0x10e0600},{0x2360123,0x10d0605},{0x680a3,0x10e0700},{0x700a3,0x10e0800},{0x680a4,0x1000700},{0x78093,0x10e0900},{0x700a4,0x1000800},{0x78094,0x1000900},{5,0}},
    {{0x8120,0xa0000},{0x9320,0xa0000},{0x105c0,0xa0000},{0x117c0,0xa0000},{0x202c0,0xa0000},{0x214c0,0xa0000},{0x304c0,0xa0000},{0x31440,0xa0000},{0x50441,0xa0000},{0x409c0,0xa0000},{0x416c0,0xa0000},{0x70441,0xa0000},{0x20143,0x600200},{0x60042,0xa0000},{0x50143,0x10e0500},{0x60123,0x10e0600},{0x23601a3,0x10d0605},{0x68123,0x10e0700},{0x70123,0x10e0800},{0x68124,0x1000700},{0x78113,0x10e0900},{0x70124,0x1000800},{0x78114,0x1000900},{5,0}},
    {{0x81a0,0xa0000},{0x93a0,0xa0000},{0x10640,0xa0000},{0x10041,0xa0000},{0x20340,0xa0000},{0x21540,0xa0000},{0x30540,0xa0000},{0x314c0,0xa0000},{0x504c1,0xa0000},{0x40a40,0xa0000},{0x41740,0xa0000},{0x704c1,0xa0000},{0x201c3,0x600200},{0x600c2,0xa0000},{0x501c3,0x10e0500},{0x601a3,0x10e0600},{0x50044,0x1000500},{0x501c4,0x1000500},{0x601a4,0x1000600},{0x60024,0x1000601},{0x681a3,0x10e0700},{0x701a3,0x10e0800},{0x681a4,0x1000700},{0x78193,0x10e0900},{0x701a4,0x1000800},{0x78194,0x1000900},{5,0}},
    {{0x8220,0xa0000},{0x9420,0xa0000},{0x106c0,0xa0000},{0x100c1,0xa0000},{0x203c0,0xa0000},{0x215c0,0xa0000},{0x305c0,0xa0000},{0x31540,0xa0000},{0x50541,0xa0000},{0x40ac0,0xa0000},{0x417c0,0xa0000},{0x70541,0xa0000},{0x20243,0x600200},{0x60142,0xa0000},{0x50243,0x10e0500},{0x60223,0x10e0600},{0x50044,0x1000501},{0x50244,0x1000500},{0x60224,0x1000600},{0x600a4,0x1000600},{0x68223,0x10e0700},{0x70223,0x10e0800},{0x68224,0x1000700},{0x78213,0x10e0900},{0x70224,0x1000800},{0x78214,0x1000900},{5,0}},
    {{0x82a0,0xa0000},{0x94a0,0xa0000},{0x10740,0xa0000},{0x10141,0xa0000},{0x20440,0xa0000},{0x21640,0xa0000},{0x30640,0xa0000},{0x315c0,0xa0000},{0x505c1,0xa0000},{0x40b40,0xa0000},{0x60041,0xa0000},{0x705c1,0xa0000},{0x508c0,0xa0000},{0x51340,0xa0000},{0x605c0,0xa0000},{0x30043,0x600300},{0x760023,0x10e0601},{0x768023,0x10e0701},{0x770023,0x10e0801},{0x68024,0x1000706},{0x778013,0x10e0901},{0x70024,0x1000804},{0x78014,0x1000902},{5,0}},
    {{0x8320,0xa0000},{0x9520,0xa0000},{0x107c0,0xa0000},{0x101c1,0xa0000},{0x204c0,0xa0000},{0x216c0,0xa0000},{0x306c0,0xa0000},{0x31640,0xa0000},{0x50641,0xa0000},{0x40bc0,0xa0000},{0x600c1,0xa0000},{0x70641,0xa0000},{0x50940,0xa0000},{0x513c0,0xa0000},{0x60640,0xa0000},{0x300c3,0x600300},{0x7600a3,0x10e0601},{0x7680a3,0x10e0701},{0x7700a3,0x10e0801},{0x680a4,0x1000701},{0x778093,0x10e0901},{0x700a4,0x1000801},{0x78094,0x1000901},{5,0}},
    {{0x83a0,0xa0000},{0x95a0,0xa0000},{0x10840,0xa0000},{0x10241,0xa0000},{0x20540,0xa0000},{0x21740,0xa0000},{0x30740,0xa0000},{0x316c0,0xa0000},{0x506c1,0xa0000},{0x40c40,0xa0000},{0x60141,0xa0000},{0x706c1,0xa0000},{0x509c0,0xa0000},{0x51440,0xa0000},{0x606c0,0xa0000},{0x30143,0x600300},{0x760123,0x10e0601},{0x768123,0x10e0701},{0x770123,0x10e0801},{0x68124,0x1000701},{0x778113,0x10e0901},{0x70124,0x1000801},{0x78114,0x1000901},{5,0}},
    {{0x8420,0xa0000},{0x9620,0xa0000},{0x108c0,0xa0000},{0x102c1,0xa0000},{0x205c0,0xa0000},{0x217c0,0xa0000},{0x307c0,0xa0000},{0x31740,0xa0000},{0x50741,0xa0000},{0x40cc0,0xa0000},{0x601c1,0xa0000},{0x70741,0xa0000},{0x50a40,0xa0000},{0x514c0,0xa0000},{0x60740,0xa0000},{0x301c3,0x600300},{0x7601a3,0x10e0601},{0x7681a3,0x10e0701},{0x7701a3,0x10e0801},{0x681a4,0x1000701},{0x778193,0x10e0901},{0x701a4,0x1000801},{0x78194,0x1000901},{5,0}},
    {{0x84a0,0xa0000},{0x96a0,0xa0000},{0x10940,0xa0000},{0x10341,0xa0000},{0x20640,0xa0000},{0x30041,0xa0000},{0x30840,0xa0000},{0x317c0,0xa0000},{0x40040,0xa0000},{0x40d40,0xa0000},{0x60241,0xa0000},{0x50040,0xa0000},{0x50ac0,0xa0000},{0x51540,0xa0000},{0x607c0,0xa0000},{0x30243,0x600300},{0x760223,0x10e0601},{0x768223,0x10e0701},{0x770223,0x10e0801},{0x68224,0x1000701},{0x778213,0x10e0901},{0x70224,0x1000801},{0x78214,0x1000901},{5,0}},
    {{0x8520,0xa0000},{0x9720,0xa0000},{0x109c0,0xa0000},{0x103c1,0xa0000},{0x206c0,0xa0000},{0x300c1,0xa0000},{0x308c0,0xa0000},{0x40041,0xa0000},{0x400c0,0xa0000},{0x40dc0,0xa0000},{0x602c1,0xa0000},{0x500c0,0xa0000},{0x50b40,0xa0000},{0x515c0,0xa0000},{0x60840,0xa0000},{0x612c0,0xa0000},{0x70540,0xa0000},{0x70fc0,0xa0000},{0x10242,0xa0000},{0xe40043,0x10e0402},{0x500c2,0xa0000},{0x40044,0x1000402},{0xe50043,0x10e0502},{0x400c4,0x1000403},{0xe60023,0x10e0602},{0x500c4,0x1000500},{0x60024,0x1000602},{0x600a4,0x1000601},{0xe68023,0x10e0702},{0xe70023,0x10e0802},{0x680a4,0x1000702},{0xe78013,0x10e0902},{0x70024,0x1000805},{0x78014,0x1000903},{5,0}},
    {{0x85a0,0xa0000},{0x97a0,0xa0000},{0x10a40,0xa0000},{0x10441,0xa0000},{0x20740,0xa0000},{0x30141,0xa0000},{0x30940,0xa0000},{0x400c1,0xa0000},{0x40140,0xa0000},{0x40e40,0xa0000},{0x60341,0xa0000},{0x50140,0xa0000},{0x50bc0,0xa0000},{0x51640,0xa0000},{0x608c0,0xa0000},{0x61340,0xa0000},{0x705c0,0xa0000},{0x71040,0xa0000},{0x20042,0xa0000},{0xe400c3,0x10e0402},{0x50142,0xa0000},{0x400c4,0x1000402},{0xe500c3,0x10e0502},{0x40144,0x1000402},{0xe600a3,0x10e0602},{0x500c4,0x1000502},{0x600a4,0x1000602},{0x60124,0x1000600},{0xe680a3,0x10e0702},{0xe700a3,0x10e0802},{0x680a4,0x1000703},{0xe78093,0x10e0902},{0x700a4,0x1000802},{0x78094,0x1000902},{5,0}},
    {{0x8620,0xa0000},{0x41,0xa0000},{0x10ac0,0xa0000},{0x104c1,0xa0000},{0x207c0,0xa0000},{0x43,0x600000},{0x60940,0xa0000},{0x613c0,0xa0000},{0x70640,0xa0000},{0x710c0,0xa0000},{0xe40143,0x10e0402},{0x20142,0xa0000},{0x60242,0xa0000},{0xe50143,0x10e0502},{0xe60123,0x10e0602},{0x50044,0x1000505},{0x50144,0x1000502},{0x60124,0x1000602},{0x60124,0x1000601},{0xe68123,0x10e0702},{0xe70123,0x10e0802},{0x68124,0x1000702},{0xe78113,0x10e0902},{0x70124,0x1000802},{0x78114,0x1000902},{5,0}},
    {{0x86a0,0xa0000},{0xc1,0xa0000},{0x10b40,0xa0000},{0x10541,0xa0000},{0x20840,0xa0000},{0xc3,0x600000},{0x609c0,0xa0000},{0x61440,0xa0000},{0x706c0,0xa0000},{0x71140,0xa0000},{0xe401c3,0x10e0402},{0x201c2,0xa0000},{0x70042,0xa0000},{0xe501c3,0x10e0502},{0xe601a3,0x10e0602},{0x50044,0x1000502},{0x501c4,0x1000502},{0x601a4,0x1000602},{0x601a4,0x1000601},{0xe681a3,0x10e0702},{0xe701a3,0x10e0802},{0x681a4,0x1000702},{0xe78193,0x10e0902},{0x701a4,0x1000802},{0x78194,0x1000902},{5,0}},
    {{0x8720,0xa0000},{0x141,0xa0000},{0x10bc0,0xa0000},{0x105c1,0xa0000},{0x208c0,0xa0000},{0x143,0x600000},{0x60a40,0xa0000},{0x614c0,0xa0000},{0x70740,0xa0000},{0x711c0,0xa0000},{0xe40243,0x10e0402},{0x20242,0xa0000},{0x700c2,0xa0000},{0xe50243,0x10e0502},{0xe60223,0x10e0602},{0x50044,0x1000504},{0x50244,0x1000502},{0x60224,0x1000602},{0x60224,0x1000601},{0xe68223,0x10e0702},{0xe70223,0x10e0802},{0x68224,0x1000702},{0xe78213,0x10e0902},{0x70224,0x1000802},{0x78214,0x1000902},{5,0}},
    {{0x87a0,0xa0000},{0x1c1,0xa0000},{0x10c40,0xa0000},{0x10641,0xa0000},{0x20940,0xa0000},{0x1c3,0x600000},{0x60ac0,0xa0000},{0x61540,0xa0000},{0x707c0,0xa0000},{0x71240,0xa0000},{0x1540043,0x10e0403},{0x30042,0xa0000},{0x70142,0xa0000},{0x1550043,0x10e0503},{0x1560023,0x10e0603},{0x50044,0x1000503},{0x50244,0x1000501},{0x60024,0x1000603},{0x1568023,0x10e0703},{0x1570023,0x10e0803},{0x680a4,0x1000704},{0x1578013,0x10e0903},{0x700a4,0x1000803},{0x78014,0x1000904},{5,0}},
    {{0x8820,0xa0000},{0x241,0xa0000},{0x10cc0,0xa0000},{0x106c1,0xa0000},{0x209c0,0xa0000},{0x243,0x600000},{0x60b40,0xa0000},{0x615c0,0xa0000},{0x70840,0xa0000},{0x712c0,0xa0000},{0x15400c3,0x10e0403},{0x300c2,0xa0000},{0x701c2,0xa0000},{0x15500c3,0x10e0503},{0x15600a3,0x10e0603},{0x50044,0x1000506},{0x500c4,0x1000503},{0x600a4,0x1000603},{0x15680a3,0x10e0703},{0x15700a3,0x10e0803},{0x680a4,0x1000705},{0x1578093,0x10e0903},{0x700a4,0x1000804},{0x78094,0x1000903},{5,0}},
    {{0x88a0,0xa0000},{0x2c1,0xa0000},{0x10d40,0xa0000},{0x10741,0xa0000},{0x20a40,0xa0000},{0x301c1,0xa0000},{0x309c0,0xa0000},{0x40141,0xa0000},{0x10043,0x600100},{0x242,0xa0000},{0x1540143,0x10e0403},{0x400c2,0xa0000},{0x40144,0x1000403},{0x1550143,0x10e0503},{0x40144,0x1000404},{0x1560123,0x10e0603},{0x50144,0x1000503},{0x60124,0x1000603},{0x1568123,0x10e0703},{0x1570123,0x10e0803},{0x68124,0x1000703},{0x1578113,0x10e0903},{0x70124,0x1000803},{0x78114,0x1000903},{5,0}},
    {{0x8920,0xa0000},{0x341,0xa0000},{0x10dc0,0xa0000},{0x20041,0xa0000},{0x20ac0,0xa0000},{0x30241,0xa0000},{0x30a40,0xa0000},{0x401c1,0xa0000},{0x100c3,0x600100},{0x10042,0xa0000},{0x15401c3,0x10e0403},{0x40142,0xa0000},{0x401c4,0x1000403},{0x15501c3,0x10e0503},{0x401c4,0x1000402},{0x15601a3,0x10e0603},{0x501c4,0x1000503},{0x601a4,0x1000603},{0x15681a3,0x10e0703},{0x15701a3,0x10e0803},{0x681a4,0x1000703},{0x1578193,0x10e0903},{0x701a4,0x1000803},{0x78194,0x1000903},{5,0}},
    {{0x89a0,0xa0000},{0x3c1,0xa0000},{0x10e40,0xa0000},{0x200c1,0xa0000},{0x20b40,0xa0000},{0x302c1,0xa0000},{0x30ac0,0xa0000},{0x40241,0xa0000},{0x10143,0x600100},{0x100c2,0xa0000},{0x1540243,0x10e0403},{0x401c2,0xa0000},{0x40244,0x1000403},{0x1550243,0x10e0503},{0x40244,0x1000402},{0x1560223,0x10e0603},{0x50244,0x1000503},{0x60224,0x1000603},{0x1568223,0x10e0703},{0x1570223,0x10e0803},{0x68224,0x1000703},{0x1578213,0x10e0903},{0x70224,0x1000803},{0x78214,0x1000903},{5,0}},
    {{0x8a20,0xa0000},{0x441,0xa0000},{0x10ec0,0xa0000},{0x20141,0xa0000},{0x20bc0,0xa0000},{0x30341,0xa0000},{0x30b40,0xa0000},{0x402c1,0xa0000},{0x101c3,0x600100},{0x10142,0xa0000},{0x1c40043,0x10e0404},{0x40242,0xa0000},{0x40044,0x1000404},{0x1c50043,0x10e0504},{0x40044,0x1000400},{0x1c60023,0x10e0604},{0x50144,0x1000500},{0x60024,0x1000604},{0x1c68023,0x10e0704},{0x1c70023,0x10e0804},{0x680a4,0x1000706},{0x1c78013,0x10e0904},{0x700a4,0x1000805},{0x78014,0x1000905},{5,0}},
    {{0x8aa0,0xa0000},{0x4c1,0xa0000},{0x10f40,0xa0000},{0x201c1,0xa0000},{0x20c40,0xa0000},{0x303c1,0xa0000},{0x30bc0,0xa0000},{0x40341,0xa0000},{0x10243,0x600100},{0x101c2,0xa0000},{0x1c400c3,0x10e0404},{0x50042,0xa0000},{0x400c4,0x1000404},{0x1c500c3,0x10e0504},{0x400c4,0x1000400},{0x1c600a3,0x10e0604},{0x500c4,0x1000504},{0x600a4,0x1000604},{0x1c680a3,0x10e0704},{0x1c700a3,0x10e0804},{0x68124,0x1000704},{0x1c78093,0x10e0904},{0x70124,0x1000804},{0x78094,0x1000904},{5,0}},
    {{0x8b20,0xa0000},{0x541,0xa0000},{0x10fc0,0xa0000},{0x20241,0xa0000},{0x20cc0,0xa0000},{0x30441,0xa0000},{0x30c40,0xa0000},{0x403c1,0xa0000},{0x401c0,0xa0000},{0x40ec0,0xa0000},{0x603c1,0xa0000},{0x501c0,0xa0000},{0x50c40,0xa0000},{0x516c0,0xa0000},{0x60bc0,0xa0000},{0x61640,0xa0000},{0x708c0,0xa0000},{0x71340,0xa0000},{0x1c40143,0x10e0404},{0x30142,0xa0000},{0x70242,0xa0000},{0x1c50143,0x10e0504},{0x1c60123,0x10e0604},{0x50144,0x1000504},{0x60124,0x1000604},{0x1c68123,0x10e0704},{0x1c70123,0x10e0804},{0x68124,0x1000705},{0x1c78113,0x10e0904},{0x70124,0x1000805},{0x78114,0x1000904},{5,0}},
    {{0x8ba0,0xa0000},{0x5c1,0xa0000},{0x11040,0xa0000},{0x202c1,0xa0000},{0x20d40,0xa0000},{0x304c1,0xa0000},{0x30cc0,0xa0000},{0x40441,0xa0000},{0x40240,0xa0000},{0x40f40,0xa0000},{0x60441,0xa0000},{0x50240,0xa0000},{0x50cc0,0xa0000},{0x51740,0xa0000},{0x60c40,0xa0000},{0x616c0,0xa0000},{0x70940,0xa0000},{0x713c0,0xa0000},{0x1c401c3,0x10e0404},{0x301c2,0xa0000},{0x401c4,0x1000404},{0x1c501c3,0x10e0504},{0x40144,0x1000400},{0x1c601a3,0x10e0604},{0x501c4,0x1000504},{0x601a4,0x1000604},{0x1c681a3,0x10e0704},{0x1c701a3,0x10e0804},{0x681a4,0x1000704},{0x1c78193,0x10e0904},{0x701a4,0x1000804},{0x78194,0x1000904},{5,0}},
    {{0x8c20,0xa0000},{0x641,0xa0000},{0x110c0,0xa0000},{0x20341,0xa0000},{0x20dc0,0xa0000},{0x30541,0xa0000},{0x30d40,0xa0000},{0x404c1,0xa0000},{0x402c0,0xa0000},{0x40fc0,0xa0000},{0x604c1,0xa0000},{0x502c0,0xa0000},{0x50d40,0xa0000},{0x517c0,0xa0000},{0x60cc0,0xa0000},{0x61740,0xa0000},{0x709c0,0xa0000},{0x71440,0xa0000},{0x1c40243,0x10e0404},{0x30242,0xa0000},{0x40244,0x1000404},{0x1c50243,0x10e0504},{0x401c4,0x1000400},{0x1c60223,0x10e0604},{0x50244,0x1000504},{0x60224,0x1000604},{0x1c68223,0x10e0704},{0x1c70223,0x10e0804},{0x68224,0x1000704},{0x1c78213,0x10e0904},{0x70224,0x1000804},{0x78214,0x1000904},{5,0}},
    {{0x8ca0,0xa0000},{0x6c1,0xa0000},{0x11140,0xa0000},{0x203c1,0xa0000},{0x20e40,0xa0000},{0x305c1,0xa0000},{0x30dc0,0xa0000},{0x40541,0xa0000},{0x40340,0xa0000},{0x41040,0xa0000},{0x60541,0xa0000},{0x50340,0xa0000},{0x50dc0,0xa0000},{0x60040,0xa0000},{0x60d40,0xa0000},{0x617c0,0xa0000},{0x70a40,0xa0000},{0x714c0,0xa0000},{0x2340043,0x10d0405},{0x7400c3,0x10e0401},{0x40044,0x1000405},{0x2350043,0x10d0505},{0x7500c3,0x10e0501},{0x501c4,0x1000501},{0x60024,0x1000605},{0x2368023,0x10d0705},{0x2370023,0x10d0805},{0x68124,0x1000706},{0x2378013,0x10d0905},{0x701a4,0x1000805},{0x78094,0x1000905},{5,0}},
    {{0x8d20,0xa0000},{0x741,0xa0000},{0x111c0,0xa0000},{0x20441,0xa0000},{0x20ec0,0xa0000},{0x30641,0xa0000},{0x30e40,0xa0000},{0x405c1,0xa0000},{0x403c0,0xa0000},{0x410c0,0xa0000},{0x605c1,0xa0000},{0x503c0,0xa0000},{0x50e40,0xa0000},{0x600c0,0xa0000},{0x60dc0,0xa0000},{0x70040,0xa0000},{0x70ac0,0xa0000},{0x71540,0xa0000},{0x23400c3,0x10d0405},{0x740143,0x10e0401},{0x400c4,0x1000405},{0x23500c3,0x10d0505},{0x750143,0x10e0501},{0x500c4,0x1000505},{0x600a4,0x1000605},{0x23680a3,0x10d0705},{0x23700a3,0x10d0805},{0x681a4,0x1000705},{0x2378093,0x10d0905},{0x70224,0x1000805},{5,0}},
    {{0x8da0,0xa0000},{0x10040,0xa0000},{0x11240,0xa0000},{0x204c1,0xa0000},{0x20f40,0xa0000},{0x306c1,0xa0000},{0x30ec0,0xa0000},{0x40641,0xa0000},{0x40440,0xa0000},{0x41140,0xa0000},{0x60641,0xa0000},{0x50440,0xa0000},{0x50ec0,0xa0000},{0x60140,0xa0000},{0x60e40,0xa0000},{0x700c0,0xa0000},{0x70b40,0xa0000},{0x715c0,0xa0000},{0x2340143,0x10d0405},{0x7401c3,0x10e0401},{0x40144,0x1000405},{0x2350143,0x10d0505},{0x7501c3,0x10e0501},{0x50144,0x1000505},{0x60124,0x1000605},{0x2368123,0x10d0705},{0x2370123,0x10d0805},{0x681a4,0x1000706},{0x2378113,0x10d0905},{0x78114,0x1000905},{5,0}},
    {{0x8e20,0xa0000},{0x100c0,0xa0000},{0x112c0,0xa0000},{0x20541,0xa0000},{0x20fc0,0xa0000},{0x30741,0xa0000},{0x30f40,0xa0000},{0x406c1,0xa0000},{0x404c0,0xa0000},{0x411c0,0xa0000},{0x606c1,0xa0000},{0x504c0,0xa0000},{0x50f40,0xa0000},{0x601c0,0xa0000},{0x60ec0,0xa0000},{0x70140,0xa0000},{0x70bc0,0xa0000},{0x71640,0xa0000},{0x23401c3,0x10d0405},{0x740243,0x10e0401},{0x401c4,0x1000405},{0x23501c3,0x10d0505},{0x750243,0x10e0501},{0x501c4,0x1000505},{0x601a4,0x1000605},{0x23681a3,0x10d0705},{0x23701a3,0x10d0805},{0x68224,0x1000705},{0x2378193,0x10d0905},{0x78194,0x1000905},{5,0}},
    {{0x8ea0,0xa0000},{0x10140,0xa0000},{0x11340,0xa0000},{0x205c1,0xa0000},{0x21040,0xa0000},{0x30040,0xa0000},{0x30fc0,0xa0000},{0x40741,0xa0000},{0x40540,0xa0000},{0x41240,0xa0000},{0x60741,0xa0000},{0x50540,0xa0000},{0x50fc0,0xa0000},{0x60240,0xa0000},{0x60f40,0xa0000},{0x701c0,0xa0000},{0x70c40,0xa0000},{0x716c0,0xa0000},{0x2340243,0x10d0405},{0x40043,0x10e0400},{0x40244,0x1000405},{0x2350243,0x10d0505},{0x400c4,0x1000401},{0x2360223,0x10d0605},{0x50244,0x1000505},{0x60224,0x1000605},{0x2368223,0x10d0705},{0x2370223,0x10d0805},{0x68224,0x1000706},{0x2378213,0x10d0905},{0x78214,0x1000905},{5,0}},
    {{0x8f20,0xa0000},{0x101c0,0xa0000},{0x113c0,0xa0000},{0x20641,0xa0000},{0x210c0,0xa0000},{0x300c0,0xa0000},{0x31040,0xa0000},{0x50041,0xa0000},{0x405c0,0xa0000},{0x412c0,0xa0000},{0x70041,0xa0000},{0x505c0,0xa0000},{0x51040,0xa0000},{0x602c0,0xa0000},{0x60fc0,0xa0000},{0x70240,0xa0000},{0x70cc0,0xa0000},{0x71740,0xa0000},{0x29c0043,0x10d0406},{0x400c3,0x10e0400},{0x40044,0x1000406},{0x29d0043,0x10d0506},{0x40144,0x1000401},{0x29e0023,0x10d0606},{0x50144,0x1000501},{0x60024,0x1000606},{0x29e8023,0x10d0706},{0x29f0023,0x10d0806},{0x29f8013,0x10d0906},{0x70024,0x1000802},{0x78014,0x1000906},{5,0}},
    {{0x8fa0,0xa0000},{0x10240,0xa0000},{0x11440,0xa0000},{0x206c1,0xa0000},{0x21140,0xa0000},{0x30140,0xa0000},{0x310c0,0xa0000},{0x500c1,0xa0000},{0x40640,0xa0000},{0x41340,0xa0000},{0x700c1,0xa0000},{0x50640,0xa0000},{0x510c0,0xa0000},{0x60340,0xa0000},{0x61040,0xa0000},{0x702c0,0xa0000},{0x70d40,0xa0000},{0x717c0,0xa0000},{0x29c00c3,0x10d0406},{0x40143,0x10e0400},{0x400c4,0x1000406},{0x29d00c3,0x10d0506},{0x401c4,0x1000401},{0x29e00a3,0x10d0606},{0x500c4,0x1000506},{0x600a4,0x1000606},{0x29e80a3,0x10d0706},{0x29f00a3,0x10d0806},{0x29f8093,0x10d0906},{0x700a4,0x1000806},{0x78094,0x1000906},{5,0}},
    {{0x9020,0xa0000},{0x102c0,0xa0000},{0x114c0,0xa0000},{0x20741,0xa0000},{0x211c0,0xa0000},{0x301c0,0xa0000},{0x31140,0xa0000},{0x50141,0xa0000},{0x406c0,0xa0000},{0x413c0,0xa0000},{0x70141,0xa0000},{0x506c0,0xa0000},{0x51140,0xa0000},{0x603c0,0xa0000},{0x610c0,0xa0000},{0x70340,0xa0000},{0x70dc0,0xa0000},{0x42,0xa0000},{0x29c0143,0x10d0406},{0x401c3,0x10e0400},{0x40144,0x1000406},{0x29d0143,0x10d0506},{0x40244,0x1000401},{0x29e0123,0x10d0606},{0x50144,0x1000506},{0x60124,0x1000606},{0x29e8123,0x10d0706},{0x29f0123,0x10d0806},{0x29f8113,0x10d0906},{0x70124,0x1000806},{0x78114,0x1000906},{5,0}},
    {{0x90a0,0xa0000},{0x10340,0xa0000},{0x11540,0xa0000},{0x20040,0xa0000},{0x21240,0xa0000},{0x30240,0xa0000},{0x311c0,0xa0000},{0x501c1,0xa0000},{0x40740,0xa0000},{0x41440,0xa0000},{0x701c1,0xa0000},{0x50740,0xa0000},{0x511c0,0xa0000},{0x60440,0xa0000},{0x61140,0xa0000},{0x703c0,0xa0000},{0x70e40,0xa0000},{0xc2,0xa0000},{0x29c01c3,0x10d0406},{0x40243,0x10e0400},{0x401c4,0x1000406},{0x29d01c3,0x10d0506},{0x40044,0x1000403},{0x29e01a3,0x10d0606},{0x501c4,0x1000506},{0x601a4,0x1000606},{0x29e81a3,0x10d0706},{0x29f01a3,0x10d0806},{0x29f8193,0x10d0906},{0x701a4,0x1000806},{0x78194,0x1000906},{5,0}},
    {{0x9120,0xa0000},{0x103c0,0xa0000},{0x115c0,0xa0000},{0x200c0,0xa0000},{0x212c0,0xa0000},{0x302c0,0xa0000},{0x31240,0xa0000},{0x50241,0xa0000},{0x407c0,0xa0000},{0x414c0,0xa0000},{0x70241,0xa0000},{0x507c0,0xa0000},{0x51240,0xa0000},{0x604c0,0xa0000},{0x611c0,0xa0000},{0x70440,0xa0000},{0x70ec0,0xa0000},{0x142,0xa0000},{0x29c0243,0x10d0406},{0x200c2,0xa0000},{0x601c2,0xa0000},{0x29d0243,0x10d0506},{0x40244,0x1000406},{0x29e0223,0x10d0606},{0x50244,0x1000506},{0x60224,0x1000606},{0x29e8223,0x10d0706},{0x29f0223,0x10d0806},{0x29f8213,0x10d0906},{0x70224,0x1000806},{0x78214,0x1000906},{5,0}},
    {{0x91a0,0xa0000},{0x10440,0xa0000},{0x11640,0xa0000},{0x20140,0xa0000},{0x21340,0xa0000},{0x30340,0xa0000},{0x312c0,0xa0000},{0x502c1,0xa0000},{0x40840,0xa0000},{0x41540,0xa0000},{0x702c1,0xa0000},{0x50840,0xa0000},{0x512c0,0xa0000},{0x60540,0xa0000},{0x61240,0xa0000},{0x704c0,0xa0000},{0x70f40,0xa0000},{0x1c2,0xa0000},{0x740043,0x10e0401},{0x40042,0xa0000},{0x40044,0x1000401},{0x750043,0x10e0501},{0x40244,0x1000400},{0x2360023,0x10d0605},{0x500c4,0x1000501},{0x60024,0x1000600},{0x68024,0x1000700},{0x68024,0x1000701},{0x68024,0x1000702},{0x68024,0x1000703},{0x68024,0x1000704},{0x70024,0x1000806},{0x70024,0x1000800},{0x70024,0x1000801},{0x78014,0x1000900},{5,0}},
}};
#define D8(i) "+f"(d[i]), "+f"(d[i + 1]), "+f"(d[i + 2]), "+f"(d[i + 3]), "+f"(d[i + 4]), "+f"(d[i + 5]), "+f"(d[i + 6]), "+f"(d[i + 7])
template <int N> __device__ __forceinline__ void wgmma_side(float* d, uint32_t alo, uint32_t blo, int sc);
template <> __device__ __forceinline__ void wgmma_side<64>(float* d, uint32_t alo, uint32_t blo, int sc) {
    asm volatile("{.reg .pred p; .reg .b64 ad, bd; setp.ne.b32 p, %34, 0; mov.b64 ad, {%32, 0x40000040}; mov.b64 bd, {%33, 0x40000040};\n"
                 "wgmma.mma_async.sync.aligned.m64n64k16.f32.bf16.bf16 "
                 "{%0,%1,%2,%3,%4,%5,%6,%7,%8,%9,%10,%11,%12,%13,%14,%15,%16,%17,%18,%19,%20,%21,%22,%23,%24,%25,%26,%27,%28,%29,%30,%31},"
                 " ad, bd, p, 1, 1, 1, 0;}"
                 : D8(0), D8(8), D8(16), D8(24)
                 : "r"(alo), "r"(blo), "r"(sc));
}
template <> __device__ __forceinline__ void wgmma_side<128>(float* d, uint32_t alo, uint32_t blo, int sc) {
    asm volatile("{.reg .pred p; .reg .b64 ad, bd; setp.ne.b32 p, %66, 0; mov.b64 ad, {%64, 0x40000040}; mov.b64 bd, {%65, 0x40000040};\n"
                 "wgmma.mma_async.sync.aligned.m64n128k16.f32.bf16.bf16 "
                 "{%0,%1,%2,%3,%4,%5,%6,%7,%8,%9,%10,%11,%12,%13,%14,%15,%16,%17,%18,%19,%20,%21,%22,%23,%24,%25,%26,%27,%28,%29,%30,%31,"
                 "%32,%33,%34,%35,%36,%37,%38,%39,%40,%41,%42,%43,%44,%45,%46,%47,%48,%49,%50,%51,%52,%53,%54,%55,%56,%57,%58,%59,%60,%61,%62,%63},"
                 " ad, bd, p, 1, 1, 1, 0;}"
                 : D8(0), D8(8), D8(16), D8(24), D8(32), D8(40), D8(48), D8(56)
                 : "r"(alo), "r"(blo), "r"(sc));
}
template <> __device__ __forceinline__ void wgmma_side<256>(float* d, uint32_t alo, uint32_t blo, int sc) {
    asm volatile("{.reg .pred p; .reg .b64 ad, bd; setp.ne.b32 p, %130, 0; mov.b64 ad, {%128, 0x40000040}; mov.b64 bd, {%129, 0x40000040};\n"
                 "wgmma.mma_async.sync.aligned.m64n256k16.f32.bf16.bf16 "
                 "{%0,%1,%2,%3,%4,%5,%6,%7,%8,%9,%10,%11,%12,%13,%14,%15,%16,%17,%18,%19,%20,%21,%22,%23,%24,%25,%26,%27,%28,%29,%30,%31,"
                 "%32,%33,%34,%35,%36,%37,%38,%39,%40,%41,%42,%43,%44,%45,%46,%47,%48,%49,%50,%51,%52,%53,%54,%55,%56,%57,%58,%59,%60,%61,%62,%63,"
                 "%64,%65,%66,%67,%68,%69,%70,%71,%72,%73,%74,%75,%76,%77,%78,%79,%80,%81,%82,%83,%84,%85,%86,%87,%88,%89,%90,%91,%92,%93,%94,%95,"
                 "%96,%97,%98,%99,%100,%101,%102,%103,%104,%105,%106,%107,%108,%109,%110,%111,%112,%113,%114,%115,%116,%117,%118,%119,%120,%121,%122,%123,%124,%125,%126,%127},"
                 " ad, bd, p, 1, 1, 1, 0;}"
                 : D8(0), D8(8), D8(16), D8(24), D8(32), D8(40), D8(48), D8(56), D8(64), D8(72), D8(80), D8(88), D8(96), D8(104), D8(112), D8(120)
                 : "r"(alo), "r"(blo), "r"(sc));
}
#undef D8

__device__ __forceinline__ void bulk_st(void* dst, uint32_t src, uint32_t bytes) {
    asm volatile("cp.async.bulk.global.shared::cta.bulk_group [%0], [%1], %2;" :: "l"(dst), "r"(src), "r"(bytes) : "memory");
}
__device__ __forceinline__ void red_release(uint32_t* p, uint32_t v) { asm volatile("red.release.gpu.global.add.u32 [%0], %1;" :: "l"(p), "r"(v) : "memory"); }
__device__ __forceinline__ void wait_ge(const uint32_t* p, uint32_t v) { for (int c = 0; c < SPIN_LIM && (int)(ld_acquire(p) - v) < 0; c++) { } }
__device__ __forceinline__ uint4* part_ptr(Job job, int wg) {
    return g_op + (size_t)((job.x >> 13) & 63) * (10 * NKS * 256) + (((job.x >> 7) & 63) * 2 + wg) * NKS * ((job.x >> 3) & 15) * 256;
}

template <int T>
__device__ __forceinline__ void side_job(Job job, uint32_t& it, uint32_t& n, uint32_t sb, uint32_t sa, int wg, int t)
{
    float acc[T / 2];
#pragma unroll
    for (int i = 0; i < T / 2; i++) acc[i] = 0.f;
    const int nkb = job.y >> 16 & 255;
    constexpr uint32_t NS = T == 64 ? 2 * SST : SST, SZ = SST * S_STAGE / NS, BO = T == 64 ? SB_FINE : 0;
    uint32_t prev = 0;
    for (int kb = 0; kb < nkb; kb++, it++) {
        const uint32_t st = it % NS;
        const uint32_t alo = ((sb + st * SZ + wg * 8192) >> 4) | (64u << 16), blo = ((sb + st * SZ + 16384) >> 4) | (1u << 16);
        mbar_wait_long(sb + SB_FULL + BO + 8 * st, (it / NS) & 1);
        wg_fence();
#pragma unroll
        for (int k4 = 0; k4 < 4; k4++) wgmma_side<T>(acc, alo + k4 * 128, blo + k4 * 2, kb | k4);
        wg_commit();
        if (kb) { wg_wait<1>(); arrive_e(prev); }
        prev = sb + SB_EMPTY + BO + 8 * st;
    }
    if (n) mbar_wait_long(sb + SB_FREE, (n - 1) & 1);
    n++;
    wg_wait<0>();
    arrive_e(prev);
    const bool raw = (job.x & 7) == JV || job.y >> 24;
#pragma unroll
    for (int u = 0; u < T / 16; u++) {
        const uint4 w = make_uint4(pack2(acc[8 * u], acc[8 * u + 1]), pack2(acc[8 * u + 2], acc[8 * u + 3]),
                                   pack2(acc[8 * u + 4], acc[8 * u + 5]), pack2(acc[8 * u + 6], acc[8 * u + 7]));
        if (raw || T != 256) sts4(sb + S_STG + wg * 32768 + t * 16 + u * 2048, make_uint4(w.x, w.z, w.y, w.w));
        else stsm4t(sb + S_STG + wg * 32768 + sa + u * 2048, w.x, w.y, w.z, w.w);
    }
    asm volatile("fence.proxy.async.shared::cta;" ::: "memory");
    __syncwarp();
    arrive_e(sb + SB_STAGED + 8 * wg);
}

__device__ __forceinline__ void ld20(const bf16* p, uint32_t* w) {
#pragma unroll
    for (int i = 0; i < 5; i++) asm volatile("ld.global.v2.b32 {%0,%1}, [%2];" : "=r"(w[2 * i]), "=r"(w[2 * i + 1]) : "l"(p + 4 * i) : "memory");
}

__global__ void __launch_bounds__(384, 1) side_kernel(const __grid_constant__ SideParams P)
{
    extern __shared__ __align__(1024) uint8_t smem[];
    const uint32_t sb = smem_u32(smem);
    const int tid = threadIdx.x, lane = tid & 31;
    const int warp = __shfl_sync(0xffffffffu, tid >> 5, 0);
    if (tid == 0) {
        for (int i = 0; i < SST; i++) { mbar_init(sb + SB_FULL + 8 * i, 1); mbar_init(sb + SB_EMPTY + 8 * i, 8); }
        for (int i = 0; i < 2 * SST; i++) { mbar_init(sb + SB_FULL + SB_FINE + 8 * i, 1); mbar_init(sb + SB_EMPTY + SB_FINE + 8 * i, 8); }
        mbar_init(sb + SB_STAGED, 4); mbar_init(sb + SB_STAGED + 8, 4); mbar_init(sb + SB_FREE, 1);
        asm volatile("fence.mbarrier_init.release.cluster;" ::: "memory");
    }
    __syncthreads();
    const Job* jobs = c_jobs.j[blockIdx.x];
    if (warp < 8) {
        asm volatile("setmaxnreg.inc.sync.aligned.u32 192;");
        const uint32_t ep = ld_epoch();
        uint32_t it = 0, it2 = 0, n = 0;
        const int wg = warp >> 2, t = tid & 127;
        const uint32_t sa = ((lane & 7) + ((lane >> 4) << 3)) * 128 + (((2 * (t >> 5) + ((lane >> 3) & 1)) ^ (lane & 7)) << 4);
        for (int j = 0; ; j++) {
            const Job job = jobs[j];
            const int type = job.x & 7, nb = (job.x >> 3) & 15;
            if (type == JEND) break;
            if (type == JR) {
                const int ks = job.y & 15, ct = (job.x >> 7) & 63;
                if (t == 0) {
                    asm volatile("cp.async.bulk.wait_group.read 0;" ::: "memory");
                    wait_ge(g_cnt + CNT_O + (job.y >> 8 & 255) * 5 + ct, ep * NKS);
                }
                bar_sync(1 + wg, 128);
                const uint4* part = part_ptr(job, wg) + ks * 128 + t;
                const uint32_t rs = sb + S_RST + wg * 6144;
                uint4 q[3][NKS];
#pragma unroll
                for (int i = 0; i < 3; i++) {
#pragma unroll
                    for (int k = 0; k < NKS; k++) q[i][k] = make_uint4(0, 0, 0, 0);
                    if (ks + i * NKS < 2 * nb) {
#pragma unroll
                        for (int k = 0; k < NKS; k++) q[i][k] = ld_pkt(part + k * nb * 256 + i * NKS * 128);
                    }
                }
#pragma unroll
                for (int i = 0; i < 3; i++)
                    if (ks + i * NKS < 2 * nb) {
                        float r[8] = {0, 0, 0, 0, 0, 0, 0, 0};
#pragma unroll
                        for (int k = 0; k < NKS; k++) {
                            r[0] += bf_lo(q[i][k].x); r[1] += bf_hi(q[i][k].x); r[2] += bf_lo(q[i][k].y); r[3] += bf_hi(q[i][k].y);
                            r[4] += bf_lo(q[i][k].z); r[5] += bf_hi(q[i][k].z); r[6] += bf_lo(q[i][k].w); r[7] += bf_hi(q[i][k].w);
                        }
                        stsm4t(rs + sa + i * 2048, pack2(r[0], r[1]), pack2(r[4], r[5]), pack2(r[2], r[3]), pack2(r[6], r[7]));
                    }
                asm volatile("fence.proxy.async.shared::cta;" ::: "memory");
                bar_sync(1 + wg, 128);
                if (t == 0) {
                    for (int i = 0; i < 3; i++)
                        if (ks + i * NKS < 2 * nb) tma_st(&P.sto, rs + i * 2048, DM + ct * 128 + wg * 64, ((job.x >> 13) & 63) * 32 + (ks + i * NKS) * 16);
                    asm volatile("cp.async.bulk.commit_group;" ::: "memory");
                }
                __syncwarp();
                continue;
            }
            switch (nb) {
                case 8: side_job<256>(job, it, n, sb, sa, wg, t); break;
                case 4: side_job<128>(job, it, n, sb, sa, wg, t); break;
                default: side_job<64>(job, it2, n, sb, sa, wg, t); break;
            }
        }
        if (t == 0) asm volatile("cp.async.bulk.wait_group 0;" ::: "memory");
    } else {
        asm volatile("setmaxnreg.dec.sync.aligned.u32 120;");
        if (warp == 8) {
            uint32_t ep = 0, ns = SST, sz = S_STAGE, bo = sb, sa = 0, pa = 1, sl = 0;
            for (int j = 0; ; j++) {
                const Job job = jobs[j];
                const int type = job.x & 7;
                if (type == JEND) break;
                if (type == JR) continue;
                const int nb = (job.x >> 3) & 15, c0 = ((job.x >> 7) & 63) * 2, seg0 = (job.x >> 13) & 63, kb0 = (job.x >> 19) & 127,
                          nkb = job.y >> 16 & 255;
                const CUtensorMap *ta = &P.a[type], *tb = nb == 8 ? &P.b[type] : &P.c[type == JV ? 0 : nb == 4 ? 1 : 2];
                auto ready = [&]() {
                    bool ok = true;
                    if (type == JP) ok = (int)(ld_acquire(g_cnt + CNT_ATT + (seg0 >> 3)) - ep * 256) >= 0;
                    else
                        for (int i = 0; i < nkb; i += 32) ok &= (int)(ld_acquire(g_prog + kb0 + min(i + lane, nkb - 1)) - (ep * 128 + seg0 + nb)) >= 0;
                    return __all_sync(0xffffffffu, ok);
                };
                if (nb == 2 && ns == SST) {
                    for (uint32_t i = 0; i < SST; i++) mbar_wait_long(sb + SB_EMPTY + 8 * i, pa ^ (i < sa));
                    ns = 2 * SST; sz = S_STAGE / 2; bo = sb + SB_FINE; sa = 0; pa = 1; sl = 0;
                }
                auto loadA = [&](int kb) {
                    const uint32_t full = bo + SB_FULL + 8 * sa;
                    mbar_wait_long(bo + SB_EMPTY + 8 * sa, pa);
                    expect_e(full, 16384 + nb * 4096);
                    tma3d_e(sb + sa * sz, ta, (kb0 + kb) * 64, c0, full);
                    if (++sa == ns) { sa = 0; pa ^= 1; }
                };
                auto loadB = [&](int kb) {
                    tma2d_e(sb + sl * sz + 16384, tb, (kb0 + kb) * 64, seg0 * 32, bo + SB_FULL + 8 * sl);
                    if (++sl == ns) sl = 0;
                };
                int pre = 0;
                if (type >= JP) {
                    if (!ready()) {
                        pre = ns;
#pragma unroll 1
                        for (int kb = 0; kb < pre; kb++) loadA(kb);
                        for (int c = 0; c < SPIN_LIM && !ready(); c++) { }
                    }
                    asm volatile("fence.proxy.async.global;" ::: "memory");
                }
#pragma unroll 1
                for (int kb = 0; kb < nkb; kb++) { if (kb >= pre) loadA(kb); loadB(kb); }
                if (j == 0) ep = ld_epoch();
            }
            asm volatile("griddepcontrol.wait;" ::: "memory");
            if (blockIdx.x == 0 && lane == 0) g_epoch = ep;
        } else if (warp == 9) {
            if (lane == 0) {
                const uint32_t ep = ld_epoch();
                uint32_t n = 0;
                for (int j = 0; ; j++) {
                    const Job job = jobs[j];
                    const int type = job.x & 7;
                    if (type == JEND) break;
                    if (type == JR) continue;
                    const int nb = (job.x >> 3) & 15, ct = (job.x >> 7) & 63, seg0 = (job.x >> 13) & 63;
                    for (int wg = 0; wg < 2; wg++) {
                        const uint32_t src = sb + S_STG + wg * 32768;
                        mbar_wait_long(sb + SB_STAGED + 8 * wg, n & 1);
                        if (type == JV) bulk_st(g_vx + ((ct * 2 + wg) * 64 + seg0) * 256, src, nb * 4096);
                        else if (job.y >> 24) bulk_st(part_ptr(job, wg) + (job.y & 15) * nb * 256, src, nb * 4096);
                        else tma_st(&P.st[type != JQ], src, (type == JO ? DM : 0) + ct * 128 + wg * 64, seg0 * 32);
                    }
                    asm volatile("cp.async.bulk.commit_group;" ::: "memory");
                    asm volatile("cp.async.bulk.wait_group.read 0;" ::: "memory");
                    mbar_arrive(sb + SB_FREE);
                    asm volatile("cp.async.bulk.wait_group 0;" ::: "memory");
                    if (type == JV) { st_release(g_flagv + ct * 128 + seg0, ep); g_flagv[ct * 128 + 64 + seg0] = ep; }
                    if (type == JQ) red_release(g_cnt + CNT_Q + (seg0 >> 3), 1);
                    if (job.y >> 24) red_release(g_cnt + CNT_O + (job.y >> 8 & 255) * 5 + ct, 1);
                    n++;
                }
            }
        } else {
            const uint32_t ep = ld_epoch();
            const float scl = 0.22360679774997896f * 1.4426950408889634f;
            for (int p = blockIdx.x * 2 + warp - 10; p < SEQ / 2; p += 2 * NSIDE) {
                const int t0 = 4 * (p >> 1) + (p & 1);
                wait_ge(g_cnt + CNT_Q + (max(t0 - 14, 0) >> 8), ep * 15);
                wait_ge(g_cnt + CNT_Q + (t0 >> 8), ep * 15);
                const bf16* base = g_qkvA + lane * 20;
                uint32_t w[18][10];
                auto row = [&](int j) { if (j < 18) ld20(base + (size_t)max(t0 + 2 - 2 * (j % 9), 0) * 1920 + (j < 9 ? 640 : 1280), w[j]); };
                float l0[8], l1[8];
                {
                    uint32_t u0[10], u1[10];
                    float q0[20], q1[20];
                    ld20(base + (size_t)t0 * 1920, u0); ld20(base + (size_t)(t0 + 2) * 1920, u1);
                    row(0); row(1);
#pragma unroll
                    for (int i = 0; i < 10; i++) { q0[2 * i] = bf_lo(u0[i]); q0[2 * i + 1] = bf_hi(u0[i]); q1[2 * i] = bf_lo(u1[i]); q1[2 * i + 1] = bf_hi(u1[i]); }
#pragma unroll
                    for (int j = 0; j < 9; j++) {
                        row(j + 2);
                        blk(warp);
                        float a0 = 0.f, a1 = 0.f;
#pragma unroll
                        for (int i = 0; i < 10; i++) {
                            const float lo = bf_lo(w[j][i]), hi = bf_hi(w[j][i]);
                            if (j > 0) a0 = fmaf(q0[2 * i + 1], hi, fmaf(q0[2 * i], lo, a0));
                            if (j < 8) a1 = fmaf(q1[2 * i + 1], hi, fmaf(q1[2 * i], lo, a1));
                        }
                        const bool in = t0 + 2 - 2 * j >= 0;
                        if (j > 0) l0[j - 1] = in ? a0 * scl : -3.0e38f;
                        if (j < 8) l1[j] = in ? a1 * scl : -3.0e38f;
                    }
                }
                float m0 = l0[0], m1 = l1[0], s0 = 0.f, s1 = 0.f;
#pragma unroll
                for (int j = 1; j < 8; j++) { m0 = fmaxf(m0, l0[j]); m1 = fmaxf(m1, l1[j]); }
#pragma unroll
                for (int j = 0; j < 8; j++) { l0[j] = ex2(l0[j] - m0); s0 += l0[j]; l1[j] = ex2(l1[j] - m1); s1 += l1[j]; }
                float o0[20], o1[20];
#pragma unroll
                for (int i = 0; i < 20; i++) o0[i] = o1[i] = 0.f;
#pragma unroll
                for (int j = 0; j < 9; j++) {
                    row(j + 11);
                    blk(warp);
#pragma unroll
                    for (int i = 0; i < 10; i++) {
                        const float lo = bf_lo(w[9 + j][i]), hi = bf_hi(w[9 + j][i]);
                        if (j > 0) { o0[2 * i] = fmaf(l0[j - 1], lo, o0[2 * i]); o0[2 * i + 1] = fmaf(l0[j - 1], hi, o0[2 * i + 1]); }
                        if (j < 8) { o1[2 * i] = fmaf(l1[j], lo, o1[2 * i]); o1[2 * i + 1] = fmaf(l1[j], hi, o1[2 * i + 1]); }
                    }
                }
                s0 = 1.f / s0; s1 = 1.f / s1;
                uint2* dst = reinterpret_cast<uint2*>(g_oA + (size_t)t0 * DM + lane * 20);
#pragma unroll
                for (int i = 0; i < 5; i++) {
                    dst[i] = make_uint2(pack2(o0[4 * i] * s0, o0[4 * i + 1] * s0), pack2(o0[4 * i + 2] * s0, o0[4 * i + 3] * s0));
                    dst[i + 2 * DM / 4] = make_uint2(pack2(o1[4 * i] * s1, o1[4 * i + 1] * s1), pack2(o1[4 * i + 2] * s1, o1[4 * i + 3] * s1));
                }
                __syncwarp();
                if (lane == 0) red_release(g_cnt + CNT_ATT + (t0 >> 8), 2);
            }
        }
    }
}

typedef CUresult (*EncodeFn)(CUtensorMap*, CUtensorMapDataType, cuuint32_t, void*, const cuuint64_t*, const cuuint64_t*,
                             const cuuint32_t*, const cuuint32_t*, CUtensorMapInterleave, CUtensorMapSwizzle,
                             CUtensorMapL2promotion, CUtensorMapFloatOOBfill);
static void make_map(EncodeFn enc, CUtensorMap* tm, const void* ptr, uint64_t cols, uint64_t rows, uint32_t bc, uint32_t br) {
    cuuint64_t dims[2] = {cols, rows}, strides[1] = {cols * 2};
    cuuint32_t box[2] = {bc, br}, es[2] = {1, 1};
    enc(tm, CU_TENSOR_MAP_DATA_TYPE_BFLOAT16, 2, const_cast<void*>(ptr), dims, strides, box, es, CU_TENSOR_MAP_INTERLEAVE_NONE,
        bc == 64 ? CU_TENSOR_MAP_SWIZZLE_128B : CU_TENSOR_MAP_SWIZZLE_64B,
        CU_TENSOR_MAP_L2_PROMOTION_L2_128B, CU_TENSOR_MAP_FLOAT_OOB_FILL_NONE);
}

static void make_map3(EncodeFn enc, CUtensorMap* tm, const void* ptr, uint64_t cols, uint64_t rows, uint32_t br, uint32_t nb) {
    cuuint64_t dims[3] = {64, rows, cols / 64}, strides[2] = {cols * 2, 128};
    cuuint32_t box[3] = {64, br, nb}, es[3] = {1, 1, 1};
    enc(tm, CU_TENSOR_MAP_DATA_TYPE_BFLOAT16, 3, const_cast<void*>(ptr), dims, strides, box, es, CU_TENSOR_MAP_INTERLEAVE_NONE, CU_TENSOR_MAP_SWIZZLE_128B,
        CU_TENSOR_MAP_L2_PROMOTION_L2_128B, CU_TENSOR_MAP_FLOAT_OOB_FILL_NONE);
}

extern "C" void kernel_launch(void* const* d_in, const int* in_sizes, int n_in, void* d_out, int out_size) {
    (void)in_sizes; (void)n_in; (void)out_size;
    const bf16* A_x = (const bf16*)d_in[0];
    const bf16* A_wqkv = (const bf16*)d_in[1];
    const bf16* A_wo = (const bf16*)d_in[2];
    const bf16* B_x = (const bf16*)d_in[3];
    const bf16* B_mem0 = (const bf16*)d_in[4];
    const bf16* B_Wq = (const bf16*)d_in[5];
    const bf16* B_Wk = (const bf16*)d_in[6];
    const bf16* B_Wv = (const bf16*)d_in[7];
    const bf16* B_Wo = (const bf16*)d_in[8];
    bf16* out = (bf16*)d_out;

    static EncodeFn enc = nullptr;
    static void *p_ox, *p_qkv, *p_oA, *p_xch;
    if (!enc) {
        void* fn = nullptr; cudaDriverEntryPointQueryResult qr;
        cudaGetDriverEntryPoint("cuTensorMapEncodeTiled", &fn, cudaEnableDefault, &qr);
        enc = (EncodeFn)fn;
        cudaFuncSetAttribute(chain_kernel, cudaFuncAttributeMaxDynamicSharedMemorySize, CHAIN_SMEM);
        cudaFuncSetAttribute(side_kernel, cudaFuncAttributeMaxDynamicSharedMemorySize, SIDE_SMEM);
        cudaGetSymbolAddress(&p_ox, g_ox); cudaGetSymbolAddress(&p_qkv, g_qkvA); cudaGetSymbolAddress(&p_oA, g_oA);
        cudaGetSymbolAddress(&p_xch, g_xch);
    }
    CUtensorMap tmXA, tmXB, tmWq, tmWk, tmWv, tmWo, tmOx;
    make_map3(enc, &tmXA, B_x, DM, SEQ, 32, NX);
    make_map3(enc, &tmXB, B_x, DM, SEQ, 32, 1);
    make_map(enc, &tmWq, B_Wq, HE, DM, 64, 128);
    make_map(enc, &tmWk, B_Wk, HE, DM, 64, 128);
    make_map(enc, &tmWv, B_Wv, HE, DM, 64, 128);
    make_map(enc, &tmWo, B_Wo, DM, HE, 32, 64);
    SideParams sp;
    make_map3(enc, &sp.a[JV], B_Wv, HE, DM, 64, 2);
    make_map3(enc, &sp.a[JQ], A_wqkv, 3 * DM, DM, 64, 2);
    make_map3(enc, &sp.a[JP], A_wo, DM, DM, 64, 2);
    make_map3(enc, &sp.a[JO], B_Wo, DM, HE, 64, 2);
    const void* act[4] = {B_x, A_x, p_oA, p_ox};
    for (int i = 0; i < 4; i++) make_map(enc, &sp.b[i], act[i], i == JO ? HE : DM, SEQ, 64, 256);
    make_map(enc, &sp.c[0], B_x, DM, SEQ, 64, 128);
    make_map(enc, &sp.c[1], p_ox, HE, SEQ, 64, 128);
    make_map(enc, &sp.c[2], p_ox, HE, SEQ, 64, 64);
    make_map(enc, &tmOx, p_ox, HE, SEQ, 64, 32);
    make_map(enc, &sp.st[0], p_qkv, 3 * DM, SEQ, 64, 256);
    make_map(enc, &sp.st[1], out, OUTW, SEQ, 64, 256);
    make_map(enc, &sp.sto, out, OUTW, SEQ, 64, 16);

    cudaStream_t st = cudaStreamPerThread;
    chain_kernel<<<96, 384, CHAIN_SMEM, st>>>(tmXA, tmXB, tmWq, tmWk, tmWv, tmWo, tmOx, B_mem0, B_x,
                                              (const char*)(((uintptr_t)p_xch + 0x1fffff) & ~(uintptr_t)0x1fffff), out);
    cudaLaunchConfig_t cfg = {};
    cfg.gridDim = dim3(NSIDE); cfg.blockDim = dim3(384); cfg.dynamicSmemBytes = SIDE_SMEM; cfg.stream = st;
    cudaLaunchAttribute at[1];
    at[0].id = cudaLaunchAttributeProgrammaticStreamSerialization; at[0].val.programmaticStreamSerializationAllowed = 1;
    cfg.attrs = at; cfg.numAttrs = 1;
    cudaLaunchKernelEx(&cfg, side_kernel, sp);
}
```

```cpp
#include <cuda_runtime.h>
#include <cuda_bf16.h>
#include <cuda.h>
#include <stdint.h>
#include <string.h>
#include <math.h>
#include <type_traits>

typedef __nv_bfloat16 bf16;

constexpr int SEQ = 2048, DM = 640, NH = 32, DH = 192, HE = NH * DH;
constexpr int NSEG = 64;
constexpr int OUTW = 1280;

__device__ uint4 g_xch[(4 << 20) / 16];
__device__ uint4 g_near4[96 * 4];
__device__ bf16  g_ox[SEQ * HE];
__device__ bf16  g_qkvA[SEQ * 3 * DM];
__device__ bf16  g_oA[SEQ * DM];
__device__ uint4 g_vx[96 * NSEG * 256];
__device__ uint4 g_op[NSEG * 70 * 256];
__device__ uint4 g_tail[2 * 32 * 80 * 32];
__device__ uint32_t g_epoch;
__device__ uint32_t g_flagv[96 * 64];
__device__ uint32_t g_prog[96];
__device__ uint32_t g_cnt[256];
constexpr int CNT_Q = 0, CNT_ATT = 8, CNT_O = 16, SPIN_LIM = 1 << 15;

__device__ __forceinline__ uint32_t smem_u32(const void* p) { return (uint32_t)__cvta_generic_to_shared(p); }
__device__ __forceinline__ uint32_t pack2(float lo, float hi) {
    uint32_t r; asm("cvt.rn.bf16x2.f32 %0, %1, %2;" : "=r"(r) : "f"(hi), "f"(lo)); return r;
}
__device__ __forceinline__ float ex2(float x) { float r; asm("ex2.approx.ftz.f32 %0, %1;" : "=f"(r) : "f"(x)); return r; }
__device__ __forceinline__ float rcpf(float x) { float r; asm("rcp.approx.ftz.f32 %0, %1;" : "=f"(r) : "f"(x)); return r; }
__device__ __forceinline__ void mbar_init(uint32_t bar, uint32_t cnt) {
    asm volatile("mbarrier.init.shared::cta.b64 [%0], %1;" :: "r"(bar), "r"(cnt) : "memory");
}
__device__ __forceinline__ void mbar_arrive(uint32_t bar) {
    asm volatile("mbarrier.arrive.shared::cta.b64 _, [%0];" :: "r"(bar) : "memory");
}
__device__ __forceinline__ void mbar_expect(uint32_t bar, uint32_t bytes) {
    asm volatile("mbarrier.arrive.expect_tx.shared::cta.b64 _, [%0], %1;" :: "r"(bar), "r"(bytes) : "memory");
}
constexpr int WAIT_LIM = 2048;
template <int N> __device__ __forceinline__ void mbar_wait_n(uint32_t bar, uint32_t parity) {
    asm volatile("{.reg .pred p, q; .reg .u32 c; mov.u32 c, %2;\n"
                 "WL_%=: sub.u32 c, c, 1; setp.eq.u32 q, c, 0; @q bra WD_%=; mbarrier.try_wait.parity.shared::cta.b64 p, [%0], %1;\n"
                 "@!p bra WL_%=; WD_%=: }" :: "r"(bar), "r"(parity), "n"(N) : "memory");
}
__device__ __forceinline__ void mbar_wait(uint32_t bar, uint32_t parity) { mbar_wait_n<1024>(bar, parity); }
__device__ __forceinline__ void mbar_wait_long(uint32_t bar, uint32_t parity) { mbar_wait_n<4096>(bar, parity); }
__device__ __forceinline__ void bar_sync(int id, int n) { asm volatile("bar.sync %0, %1;" :: "r"(id), "r"(n) : "memory"); }
__device__ __forceinline__ void bar_arrive(int id, int n) { asm volatile("bar.arrive %0, %1;" :: "r"(id), "r"(n) : "memory"); }
__device__ __forceinline__ void tma2d(uint32_t dst, const CUtensorMap* tm, int c0, int c1, uint32_t bar) {
    asm volatile("cp.async.bulk.tensor.2d.shared::cluster.global.mbarrier::complete_tx::bytes [%0], [%1, {%3, %4}], [%2];"
                 :: "r"(dst), "l"(tm), "r"(bar), "r"(c0), "r"(c1) : "memory");
}
__device__ __forceinline__ void tma_st(const CUtensorMap* tm, uint32_t src, int c0, int c1) {
    asm volatile("cp.async.bulk.tensor.2d.global.shared::cta.bulk_group [%0, {%2, %3}], [%1];" :: "l"(tm), "r"(src), "r"(c0), "r"(c1) : "memory");
}
__device__ __forceinline__ void ldsm4(uint32_t a, uint32_t& r0, uint32_t& r1, uint32_t& r2, uint32_t& r3) {
    asm volatile("ldmatrix.sync.aligned.m8n8.x4.shared.b16 {%0,%1,%2,%3}, [%4];"
                 : "=r"(r0), "=r"(r1), "=r"(r2), "=r"(r3) : "r"(a) : "memory");
}
__device__ __forceinline__ void ldsm4t(uint32_t a, uint32_t& r0, uint32_t& r1, uint32_t& r2, uint32_t& r3) {
    asm volatile("ldmatrix.sync.aligned.m8n8.x4.trans.shared.b16 {%0,%1,%2,%3}, [%4];"
                 : "=r"(r0), "=r"(r1), "=r"(r2), "=r"(r3) : "r"(a) : "memory");
}
__device__ __forceinline__ void ldsm2t(uint32_t a, uint32_t& r0, uint32_t& r1) {
    asm volatile("ldmatrix.sync.aligned.m8n8.x2.trans.shared.b16 {%0,%1}, [%2];" : "=r"(r0), "=r"(r1) : "r"(a) : "memory");
}
__device__ __forceinline__ void stsm4t(uint32_t a, uint32_t r0, uint32_t r1, uint32_t r2, uint32_t r3) {
    asm volatile("stmatrix.sync.aligned.m8n8.x4.trans.shared.b16 [%0], {%1,%2,%3,%4};"
                 :: "r"(a), "r"(r0), "r"(r1), "r"(r2), "r"(r3) : "memory");
}
__device__ __forceinline__ void stsm4(uint32_t a, uint32_t r0, uint32_t r1, uint32_t r2, uint32_t r3) {
    asm volatile("stmatrix.sync.aligned.m8n8.x4.shared.b16 [%0], {%1,%2,%3,%4};"
                 :: "r"(a), "r"(r0), "r"(r1), "r"(r2), "r"(r3) : "memory");
}
__device__ __forceinline__ void stsm2t(uint32_t a, uint32_t r0, uint32_t r1) {
    asm volatile("stmatrix.sync.aligned.m8n8.x2.trans.shared.b16 [%0], {%1,%2};" :: "r"(a), "r"(r0), "r"(r1) : "memory");
}
__device__ __forceinline__ uint32_t movm(uint32_t a) {
    uint32_t d; asm volatile("movmatrix.sync.aligned.m8n8.trans.b16 %0, %1;" : "=r"(d) : "r"(a)); return d;
}
__device__ __forceinline__ void mma16(float* c, uint32_t a0, uint32_t a1, uint32_t a2, uint32_t a3, uint32_t b0, uint32_t b1) {
    asm volatile("mma.sync.aligned.m16n8k16.row.col.f32.bf16.bf16.f32 {%0,%1,%2,%3}, {%4,%5,%6,%7}, {%8,%9}, {%0,%1,%2,%3};"
                 : "+f"(c[0]), "+f"(c[1]), "+f"(c[2]), "+f"(c[3]) : "r"(a0), "r"(a1), "r"(a2), "r"(a3), "r"(b0), "r"(b1));
}
__device__ __forceinline__ void mma8(float* c, uint32_t a0, uint32_t a1, uint32_t b0) {
    asm volatile("mma.sync.aligned.m16n8k8.row.col.f32.bf16.bf16.f32 {%0,%1,%2,%3}, {%4,%5}, {%6}, {%0,%1,%2,%3};"
                 : "+f"(c[0]), "+f"(c[1]), "+f"(c[2]), "+f"(c[3]) : "r"(a0), "r"(a1), "r"(b0));
}
__device__ __forceinline__ void wg_fence() { asm volatile("wgmma.fence.sync.aligned;" ::: "memory"); }
__device__ __forceinline__ void wg_commit() { asm volatile("wgmma.commit_group.sync.aligned;" ::: "memory"); }
template <int N> __device__ __forceinline__ void wg_wait() { asm volatile("wgmma.wait_group.sync.aligned %0;" :: "n"(N) : "memory"); }
__device__ __forceinline__ uint64_t mkdesc(uint32_t addr, uint32_t lbo, uint32_t sbo, uint32_t swz) {
    return (uint64_t)((addr & 0x3FFFF) >> 4) | ((uint64_t)(lbo >> 4) << 16) | ((uint64_t)(sbo >> 4) << 32) | ((uint64_t)swz << 62);
}
template <int BOFF, int SC>
__device__ __forceinline__ void wgmma_rs16(float* d, uint32_t a0, uint32_t a1, uint32_t a2, uint32_t a3, uint32_t blo) {
    asm volatile("{.reg .pred p; .reg .b32 l; .reg .b64 bd; setp.ne.b32 p, %14, 0; add.u32 l, %12, %13; mov.b64 bd, {l, 40};\n"
                 "wgmma.mma_async.sync.aligned.m64n16k16.f32.bf16.bf16 {%0,%1,%2,%3,%4,%5,%6,%7}, {%8,%9,%10,%11}, bd, p, 1, 1, 0;}"
                 : "+f"(d[0]), "+f"(d[1]), "+f"(d[2]), "+f"(d[3]), "+f"(d[4]), "+f"(d[5]), "+f"(d[6]), "+f"(d[7])
                 : "r"(a0), "r"(a1), "r"(a2), "r"(a3), "r"(blo), "n"(BOFF), "n"(SC));
}
template <int BOFF, int SC>
__device__ __forceinline__ void wgmma_rs32n(float* d, uint32_t a0, uint32_t a1, uint32_t a2, uint32_t a3, uint32_t blo) {
    asm volatile("{.reg .pred p; .reg .b32 l; .reg .b64 bd; setp.ne.b32 p, %22, 0; add.u32 l, %20, %21; mov.b64 bd, {l, 40};\n"
                 "wgmma.mma_async.sync.aligned.m64n32k16.f32.bf16.bf16 "
                 "{%0,%1,%2,%3,%4,%5,%6,%7,%8,%9,%10,%11,%12,%13,%14,%15}, {%16,%17,%18,%19}, bd, p, 1, 1, 0;}"
                 : "+f"(d[0]), "+f"(d[1]), "+f"(d[2]), "+f"(d[3]), "+f"(d[4]), "+f"(d[5]), "+f"(d[6]), "+f"(d[7]),
                   "+f"(d[8]), "+f"(d[9]), "+f"(d[10]), "+f"(d[11]), "+f"(d[12]), "+f"(d[13]), "+f"(d[14]), "+f"(d[15])
                 : "r"(a0), "r"(a1), "r"(a2), "r"(a3), "r"(blo), "n"(BOFF), "n"(SC));
}
template <int BOFF, int SC>
__device__ __forceinline__ void wgmma_rs32(float* d, uint32_t a0, uint32_t a1, uint32_t a2, uint32_t a3, uint32_t blo) {
    asm volatile("{.reg .pred p; .reg .b32 l; .reg .b64 bd; setp.ne.b32 p, %22, 0; add.u32 l, %20, %21; mov.b64 bd, {l, 0x40000040};\n"
                 "wgmma.mma_async.sync.aligned.m64n32k16.f32.bf16.bf16 "
                 "{%0,%1,%2,%3,%4,%5,%6,%7,%8,%9,%10,%11,%12,%13,%14,%15}, {%16,%17,%18,%19}, bd, p, 1, 1, 0;}"
                 : "+f"(d[0]), "+f"(d[1]), "+f"(d[2]), "+f"(d[3]), "+f"(d[4]), "+f"(d[5]), "+f"(d[6]), "+f"(d[7]),
                   "+f"(d[8]), "+f"(d[9]), "+f"(d[10]), "+f"(d[11]), "+f"(d[12]), "+f"(d[13]), "+f"(d[14]), "+f"(d[15])
                 : "r"(a0), "r"(a1), "r"(a2), "r"(a3), "r"(blo), "n"(BOFF), "n"(SC));
}
template <int AOFF, int BOFF, int SC>
__device__ __forceinline__ void wgmma_ss32(float* d, uint32_t alo, uint32_t blo) {
    asm volatile("{.reg .pred p; .reg .b32 l, m; .reg .b64 ad, bd; setp.ne.b32 p, %20, 0; add.u32 l, %16, %18; add.u32 m, %17, %19;\n"
                 "mov.b64 ad, {l, 0x40000040}; mov.b64 bd, {m, 0x40000040};\n"
                 "wgmma.mma_async.sync.aligned.m64n32k16.f32.bf16.bf16 "
                 "{%0,%1,%2,%3,%4,%5,%6,%7,%8,%9,%10,%11,%12,%13,%14,%15}, ad, bd, p, 1, 1, 1, 0;}"
                 : "+f"(d[0]), "+f"(d[1]), "+f"(d[2]), "+f"(d[3]), "+f"(d[4]), "+f"(d[5]), "+f"(d[6]), "+f"(d[7]),
                   "+f"(d[8]), "+f"(d[9]), "+f"(d[10]), "+f"(d[11]), "+f"(d[12]), "+f"(d[13]), "+f"(d[14]), "+f"(d[15])
                 : "r"(alo), "r"(blo), "n"(AOFF), "n"(BOFF), "n"(SC));
}
template <int AOFF, int BOFF, int SC>
__device__ __forceinline__ void wgmma_ss8(float* d, uint32_t alo, uint32_t blo) {
    asm volatile("{.reg .pred p; .reg .b32 l, m; .reg .b64 ad, bd; setp.ne.b32 p, %8, 0; add.u32 l, %4, %6; add.u32 m, %5, %7;\n"
                 "mov.b64 ad, {l, 0x40000040}; mov.b64 bd, {m, 0x8};\n"
                 "wgmma.mma_async.sync.aligned.m64n8k16.f32.bf16.bf16 {%0,%1,%2,%3}, ad, bd, p, 1, 1, 1, 1;}"
                 : "+f"(d[0]), "+f"(d[1]), "+f"(d[2]), "+f"(d[3]) : "r"(alo), "r"(blo), "n"(AOFF), "n"(BOFF), "n"(SC));
}
template <int OFF, int SC>
__device__ __forceinline__ void wgmma_ss40(float* d, uint32_t alo, uint32_t blo) {
    asm volatile("{.reg .pred p; .reg .b32 l, m; .reg .b64 ad, bd; setp.ne.b32 p, %23, 0; add.u32 l, %20, %22; add.u32 m, %21, %22;\n"
                 "mov.b64 ad, {l, 0x40000020}; mov.b64 bd, {m, 0x40000040};\n"
                 "wgmma.mma_async.sync.aligned.m64n40k16.f32.bf16.bf16 "
                 "{%0,%1,%2,%3,%4,%5,%6,%7,%8,%9,%10,%11,%12,%13,%14,%15,%16,%17,%18,%19}, ad, bd, p, 1, 1, 0, 0;}"
                 : "+f"(d[0]), "+f"(d[1]), "+f"(d[2]), "+f"(d[3]), "+f"(d[4]), "+f"(d[5]), "+f"(d[6]), "+f"(d[7]),
                   "+f"(d[8]), "+f"(d[9]), "+f"(d[10]), "+f"(d[11]), "+f"(d[12]), "+f"(d[13]), "+f"(d[14]), "+f"(d[15]),
                   "+f"(d[16]), "+f"(d[17]), "+f"(d[18]), "+f"(d[19])
                 : "r"(alo), "r"(blo), "n"(OFF), "n"(SC));
}
template <int I> using IC = std::integral_constant<int, I>;
template <int I, int N, class F> __device__ __forceinline__ void static_for(F&& f) {
    if constexpr (I < N) { f(std::integral_constant<int, I>{}); static_for<I + 1, N>(f); }
}
__device__ __forceinline__ uint32_t mapa(uint32_t a, uint32_t rank) {
    uint32_t r; asm("mapa.shared::cluster.u32 %0, %1, %2;" : "=r"(r) : "r"(a), "r"(rank)); return r;
}
__device__ __forceinline__ void st_async2(uint32_t a, uint32_t x, uint32_t y, uint32_t bar) {
    asm volatile("st.async.weak.shared::cluster.mbarrier::complete_tx::bytes.v2.b32 [%0], {%1,%2}, [%3];"
                 :: "r"(a), "r"(x), "r"(y), "r"(bar) : "memory");
}
__device__ __forceinline__ void st_async1(uint32_t a, uint32_t x, uint32_t bar) {
    asm volatile("st.async.weak.shared::cluster.mbarrier::complete_tx::bytes.b32 [%0], %1, [%2];" :: "r"(a), "r"(x), "r"(bar) : "memory");
}
__device__ __forceinline__ void st_async4(uint32_t a, uint32_t x, uint32_t y, uint32_t z, uint32_t w, uint32_t bar) {
    asm volatile("st.async.weak.shared::cluster.mbarrier::complete_tx::bytes.v4.b32 [%0], {%1,%2,%3,%4}, [%5];"
                 :: "r"(a), "r"(x), "r"(y), "r"(z), "r"(w), "r"(bar) : "memory");
}
__device__ __forceinline__ void sts2(uint32_t a, uint32_t x, uint32_t y) {
    asm volatile("st.shared.v2.b32 [%0], {%1,%2};" :: "r"(a), "r"(x), "r"(y) : "memory");
}
__device__ __forceinline__ void sts4(uint32_t a, uint4 v) {
    asm volatile("st.shared.v4.b32 [%0], {%1,%2,%3,%4};" :: "r"(a), "r"(v.x), "r"(v.y), "r"(v.z), "r"(v.w) : "memory");
}
__device__ __forceinline__ void sts1(uint32_t a, uint32_t x) { asm volatile("st.shared.b32 [%0], %1;" :: "r"(a), "r"(x) : "memory"); }
__device__ __forceinline__ float2 lds2f(uint32_t a) {
    float2 v; asm volatile("ld.shared.v2.f32 {%0,%1}, [%2];" : "=f"(v.x), "=f"(v.y) : "r"(a) : "memory"); return v;
}
__device__ __forceinline__ uint4 lds4(uint32_t a) {
    uint4 v; asm volatile("ld.shared.v4.b32 {%0,%1,%2,%3}, [%4];" : "=r"(v.x), "=r"(v.y), "=r"(v.z), "=r"(v.w) : "r"(a) : "memory"); return v;
}
__device__ __forceinline__ uint32_t lds1(uint32_t a) {
    uint32_t v; asm volatile("ld.shared.b32 %0, [%1];" : "=r"(v) : "r"(a) : "memory"); return v;
}
__device__ __forceinline__ void stg1(void* p, uint32_t x) { asm volatile("st.global.b32 [%0], %1;" :: "l"(p), "r"(x) : "memory"); }
__device__ __forceinline__ uint32_t ld_acquire(const uint32_t* p) {
    uint32_t v; asm volatile("ld.acquire.gpu.global.u32 %0, [%1];" : "=r"(v) : "l"(p) : "memory"); return v;
}
__device__ __forceinline__ uint32_t ld_relaxed(const void* p) {
    uint32_t v; asm volatile("ld.relaxed.gpu.global.u32 %0, [%1];" : "=r"(v) : "l"(p) : "memory"); return v;
}
__device__ __forceinline__ uint32_t ld_epoch() {
    uint32_t v; asm volatile("ld.relaxed.gpu.global.u32 %0, [%1];" : "=r"(v) : "l"(&g_epoch) : "memory"); return v + 1;
}
__device__ __forceinline__ void st_release(uint32_t* p, uint32_t v) { asm volatile("st.release.gpu.global.u32 [%0], %1;" :: "l"(p), "r"(v) : "memory"); }
__device__ __forceinline__ void st_pkt8(const void* p, uint32_t x, uint32_t y) {
    asm volatile("{.reg .b64 v; mov.b64 v, {%1,%2}; st.relaxed.gpu.global.b64 [%0], v;}" :: "l"(p), "r"(x), "r"(y) : "memory");
}
__device__ __forceinline__ void st_pkt4(const void* p, uint32_t x) {
    asm volatile("st.relaxed.gpu.global.b32 [%0], %1;" :: "l"(p), "r"(x) : "memory");
}
__device__ __forceinline__ uint4 ld_pkt(const void* p) {
    uint4 r;
    asm volatile("{.reg .b64 lo, hi; .reg .b128 v; ld.relaxed.gpu.global.b128 v, [%4]; mov.b128 {lo, hi}, v;\n"
                 "mov.b64 {%0,%1}, lo; mov.b64 {%2,%3}, hi;}"
                 : "=r"(r.x), "=r"(r.y), "=r"(r.z), "=r"(r.w) : "l"(p) : "memory");
    return r;
}

template <int OFF> __device__ __forceinline__ void ld_pkt_stale(uint4& r, const void* p, uint32_t tag) {
    asm volatile("{.reg .pred p; .reg .b32 t; .reg .b64 lo, hi; .reg .b128 v; lop3.b32 t, %0, %5, 1, 0x28; setp.ne.u32 p, t, 0;\n"
                 "mov.b64 lo, {%0,%1}; mov.b64 hi, {%2,%3}; mov.b128 v, {lo, hi}; @p ld.relaxed.gpu.global.b128 v, [%4 + %6];\n"
                 "mov.b128 {lo, hi}, v; mov.b64 {%0,%1}, lo; mov.b64 {%2,%3}, hi;}"
                 : "+r"(r.x), "+r"(r.y), "+r"(r.z), "+r"(r.w) : "l"(p), "r"(tag), "n"(OFF) : "memory");
}

constexpr int NX = 7;
constexpr uint32_t OFF_WV = 0, OFF_WO = 81920, OFF_XR = OFF_WO + 86016, OFF_QA = OFF_XR + NX * 4096, OFF_SP = OFF_QA + 5120, OFF_RED = OFF_SP,
                   OFF_BAR = OFF_SP + 2560, OFF_KA = OFF_QA + 8192, OFF_MEMT = OFF_KA + 5120, OFF_SM = OFF_MEMT + 10240, OFF_PM = OFF_SM + 1280,
                   OFF_SX = OFF_PM + 768, OFF_R1 = OFF_SX + 5120, OFF_OX = OFF_R1, OFF_DBG = OFF_R1 + 4096, CHAIN_SMEM = OFF_DBG + 1024,
                   OFF_OXL = OFF_XR, OFF_OXG = OFF_XR + 4096, OFF_R1L = OFF_XR + 20480, OFF_TRED = OFF_WV + 32768;
__host__ __device__ constexpr uint32_t xblk(int kb) { return kb < 3 ? OFF_MEMT - OFF_XR + kb * 4096 : (kb - 3) * 4096; }
constexpr uint32_t MB_S = OFF_BAR, MB_SX = OFF_BAR + 8, MB_O = OFF_BAR + 16, MB_WO = OFF_BAR + 24, MB_XA = OFF_BAR + 32, MB_XB = OFF_BAR + 40,
                   MB_M = OFF_BAR + 48, MB_EM = OFF_BAR + 88, MB_EA = OFF_BAR + 96, OFF_EP = OFF_BAR + 112,
                   MB_F = OFF_BAR + 128, MB_E = OFF_BAR + 168, OFF_ROLE = OFF_BAR + 224, OFF_T = OFF_BAR + 232, OFF_SPO = OFF_BAR + 236, MB_M2 = OFF_BAR + 240;
constexpr int BAR_QM = 0, BAR_PUB = 1, BAR_QK = 2, BAR_P = 3, BAR_WO = 4, BAR_S = 5, BAR_O2 = 6, BAR_O = 7, BAR_R = 8, BAR_PM = 9, BAR_G = 10,
              BAR_X = 15, BAR_R1 = 15, BAR_MEM = 11;
constexpr float SCL_B = 0.07216878364870322f * 1.4426950408889634f;
#define NPROBE 3
#define G1 1056
#define G2 1568
#define F1 0
#define F2 1
#define BN 9
#define BD 1
#define NVR 4
#define NVP 6
#define NVE 6
#define NPF 11
#define NPE 1
#define NPM 7
#define PFV 1
#define PFX 1
#define PROG 0x5111010101010100ull
#define LEAD 2
#define NV0 3
#define HV 1
#define REL 2
#define RB 1
#define TXD 300
#define TXE 0
#define WOK 0x888
#define AJ 2
#define KJ 9
#define XG 1
#define VFLAGS 0x101010101010444ull
#define SD 0
#define NOB 4
#define PW0 7
#define PW1 4
#define NVC 2
#define PWIN 2
#define NCP 1

static_assert((VFLAGS & ((4ull << NVC) - 1)) == 1ull << NVC, "first block of v");
__device__ __forceinline__ uint32_t clk32() { uint32_t c; asm volatile("mov.u32 %0, %%clock;" : "=r"(c)); return c; }
__device__ __forceinline__ void spin(uint32_t n) { const uint32_t t = clk32(); while (clk32() - t < n) { } }
__device__ __forceinline__ uint32_t gtime() { uint32_t c; asm volatile("mov.u32 %0, %%globaltimer_lo;" : "=r"(c)); return c; }
__device__ __forceinline__ void ggate(uint32_t t) { while ((int)(gtime() - t) < 0) { } }
template <int N> __device__ __forceinline__ void pause() {
    if constexpr (N > 0) {
        uint32_t x = clk32();
#pragma unroll
        for (int i = 1; i < N; i++) asm volatile("mad.lo.u32 %0, %0, %0, %0;" : "+r"(x));
        asm volatile("{.reg .pred p; .reg .b32 t; mad.lo.u32 t, %0, %0, %0; setp.eq.u32 p, t, 1; @p exit;}" :: "r"(x) : "memory");
    }
}
__device__ __forceinline__ uint32_t laneid() { uint32_t c; asm volatile("mov.u32 %0, %%laneid;" : "=r"(c)); return c; }
template <int K> __device__ __forceinline__ uint32_t opq0(uint32_t s) { uint32_t c; asm volatile("shr.u32 %0, %1, %2;" : "=r"(c) : "r"(s), "n"(K)); return c; }
__device__ __forceinline__ uint32_t keep(uint32_t x) { asm volatile("" : "+r"(x)); return x; }
template <class T> __device__ __forceinline__ T* keepp(T* p) { asm volatile("" : "+l"(p)); return p; }
__device__ __forceinline__ void sched() { asm volatile("bar.warp.sync 0xffffffff;" ::: "memory"); }
__device__ __forceinline__ void blk(int s) { asm volatile("{.reg .pred p; setp.gt.s32 p, %0, 1000; @p exit;}" :: "r"(s) : "memory"); }
__device__ __forceinline__ uint32_t selu(bool c, uint32_t a, uint32_t b) {
    uint32_t r; asm("{.reg .pred p; setp.ne.u32 p, %1, 0; selp.b32 %0, %2, %3, p;}" : "=r"(r) : "r"((uint32_t)c), "r"(a), "r"(b)); return r;
}
__device__ __forceinline__ float bf_lo(uint32_t w) { return __uint_as_float(w << 16); }
__device__ __forceinline__ float bf_hi(uint32_t w) { return __uint_as_float(w & 0xffff0000u); }
__device__ __forceinline__ uint32_t badd2(uint32_t a, uint32_t b) { uint32_t r; asm("add.rn.bf16x2 %0, %1, %2;" : "=r"(r) : "r"(a), "r"(b)); return r; }
__device__ __forceinline__ uint32_t tagx(uint32_t a, uint32_t b, uint32_t t) { uint32_t r; asm("lop3.b32 %0, %1, %2, %3, 0x7e;" : "=r"(r) : "r"(a), "r"(t), "r"(b)); return r; }
__device__ __forceinline__ uint32_t tagv(uint32_t a, uint32_t b, uint32_t t) { uint32_t r; asm volatile("lop3.b32 %0, %1, %2, %3, 0x7e;" : "=r"(r) : "r"(a), "r"(t), "r"(b)); return r; }
__device__ __forceinline__ uint32_t or3(uint32_t a, uint32_t b, uint32_t c) { uint32_t r; asm("lop3.b32 %0, %1, %2, %3, 0xfe;" : "=r"(r) : "r"(a), "r"(b), "r"(c)); return r; }
__device__ __forceinline__ bool any_bit0(uint32_t a, uint32_t b) {
    uint32_t r;
    asm volatile("{.reg .pred p; .reg .b32 t; lop3.b32 t, %1, 1, %2, 0xc8; setp.ne.u32 p, t, 0; vote.sync.any.pred p, p, 0xffffffff; selp.u32 %0, 1, 0, p;}"
                 : "=r"(r) : "r"(a), "r"(b));
    return r;
}
__device__ __forceinline__ void arrive_e(uint32_t bar) {
    asm volatile("{.reg .pred p; elect.sync _|p, 0xffffffff; @p mbarrier.arrive.shared::cta.b64 _, [%0];}" :: "r"(bar) : "memory");
}
__device__ __forceinline__ void expect_e(uint32_t bar, uint32_t bytes) {
    asm volatile("{.reg .pred p; elect.sync _|p, 0xffffffff; @p mbarrier.arrive.expect_tx.shared::cta.b64 _, [%0], %1;}" :: "r"(bar), "r"(bytes) : "memory");
}
__device__ __forceinline__ void tma2d_e(uint32_t dst, const CUtensorMap* tm, int c0, int c1, uint32_t bar) {
    asm volatile("{.reg .pred p; elect.sync _|p, 0xffffffff;\n"
                 "@p cp.async.bulk.tensor.2d.shared::cluster.global.mbarrier::complete_tx::bytes [%0], [%1, {%3, %4}], [%2];}"
                 :: "r"(dst), "l"(tm), "r"(bar), "r"(c0), "r"(c1) : "memory");
}
__device__ __forceinline__ void ldsm4_if(bool c, uint32_t a, uint32_t& r0, uint32_t& r1, uint32_t& r2, uint32_t& r3) {
    asm volatile("{.reg .pred p; setp.ne.u32 p, %5, 0; @p ldmatrix.sync.aligned.m8n8.x4.shared.b16 {%0,%1,%2,%3}, [%4];}"
                 : "+r"(r0), "+r"(r1), "+r"(r2), "+r"(r3) : "r"(a), "r"((uint32_t)c) : "memory");
}
__device__ __forceinline__ bool arrive_unless(uint32_t a, uint32_t m, int bar, int n) {
    uint32_t r;
    asm volatile("{.reg .pred p; .reg .b32 t; and.b32 t, %1, %2; setp.ne.u32 p, t, 0; vote.sync.any.pred p, p, 0xffffffff; @!p bar.arrive %3, %4;"
                 " selp.u32 %0, 1, 0, p;}" : "=r"(r) : "r"(a), "r"(m), "r"(bar), "r"(n) : "memory");
    return r;
}
__device__ __forceinline__ bool sync_unless(uint32_t a, uint32_t b, uint32_t m, int bar, int n) {
    uint32_t r;
    asm volatile("{.reg .pred p; .reg .b32 t; lop3.b32 t, %1, %2, %3, 0xa8; setp.ne.u32 p, t, 0; vote.sync.any.pred p, p, 0xffffffff; @!p bar.sync %4, %5;"
                 " selp.u32 %0, 1, 0, p;}" : "=r"(r) : "r"(a), "r"(b), "r"(m), "n"(BAR_R), "n"(128) : "memory");
    return r;
}
__device__ __forceinline__ uint32_t pack2v(float lo, float hi) {
    uint32_t r; asm volatile("cvt.rn.bf16x2.f32 %0, %1, %2;" : "=r"(r) : "f"(hi), "f"(lo)); return r;
}
__device__ __forceinline__ void st_pkt(const void* p, uint4 v) {
    asm volatile("{.reg .b64 lo, hi; .reg .b128 v; mov.b64 lo, {%1,%2}; mov.b64 hi, {%3,%4}; mov.b128 v, {lo, hi}; st.relaxed.gpu.global.b128 [%0], v;}"
                 :: "l"(p), "r"(v.x), "r"(v.y), "r"(v.z), "r"(v.w) : "memory");
}
__device__ __forceinline__ void bulk_ld_e(uint32_t dst, const void* src, uint32_t bytes, uint32_t bar) {
    asm volatile("{.reg .pred p; elect.sync _|p, 0xffffffff;\n"
                 "@p cp.async.bulk.shared::cluster.global.mbarrier::complete_tx::bytes [%0], [%1], %2, [%3];}"
                 :: "r"(dst), "l"(src), "r"(bytes), "r"(bar) : "memory");
}
template <int OFF> __device__ __forceinline__ void ld_pkt8(uint32_t& x, uint32_t& y, const void* p) {
    asm volatile("{.reg .b64 v; ld.relaxed.gpu.global.b64 v, [%2 + %3]; mov.b64 {%0,%1}, v;}" : "=r"(x), "=r"(y) : "l"(p), "n"(OFF) : "memory");
}
__device__ __forceinline__ void tma3d_e(uint32_t dst, const CUtensorMap* tm, int c1, int c2, uint32_t bar) {
    asm volatile("{.reg .pred p; elect.sync _|p, 0xffffffff;\n"
                 "@p cp.async.bulk.tensor.3d.shared::cluster.global.mbarrier::complete_tx::bytes [%0], [%1, {0, %3, %4}], [%2];}"
                 :: "r"(dst), "l"(tm), "r"(bar), "r"(c1), "r"(c2) : "memory");
}

constexpr uint32_t XCH_PART = 0x80000;
__device__ __forceinline__ uint32_t xch_line(uint32_t r) { return r ^ ((1 ^ r >> 1 ^ r >> 4 ^ r >> 5) & 1); }
__host__ __device__ constexpr uint32_t xch_mem(uint32_t cg) { return 0x48000 + (cg & 1) * 0x4000 + (cg >> 1) * 0x100000; }
__host__ __device__ constexpr uint32_t xch_copy(uint32_t k) { return (0x22123000u >> 8 * k & 255) << 12; }
__device__ __forceinline__ uint32_t mem_row(uint32_t c) { return (c & 16) * 16 + (c & 4) * 32 + ((((c >> 1) ^ c) & 4) | (c & 3)) * 16; }

#define BORD 0xcb43a29180ull
__host__ __device__ constexpr int bulk_ord(int h) { return (BORD >> 4 * h) & 15; }
__host__ __device__ constexpr int bulk_pos(int k) {
    int r = -1;
    for (int h = 0; h < 10; h++) {
        const int v = bulk_ord(h);
        if ((k == 0 ? (v & 7) == 2 : k == 3 ? (v & 7) < 3 : (v >> 3) == (k == 2)) && (k >= 3 || r < 0)) r = h;
    }
    return r;
}

__device__ __forceinline__ void set_role(uint32_t sb, uint32_t r) {
    const uint32_t role = xch_line(r);
    sts1(sb + OFF_ROLE, role | (xch_mem((role & 255) / 20) + ((role & 255) % 20) * 128) << 2);
    sts1(sb + OFF_SPO, 0x44000 + xch_copy(1 + (role >> 1 & 1)) + (role >> 8) * 4096);
}
__device__ __forceinline__ void pick_role(uint32_t sb, bool second, uint32_t page, const char* pp, uint32_t ep) {
    uint32_t* const g_near = reinterpret_cast<uint32_t*>(g_near4);
    const uint32_t ln = laneid();
    if (!second) {
        if (ln == 0) {
            uint32_t t = 4095;
#pragma unroll 1
            for (int i = 0; i < NPROBE; i++) {
                const uint32_t c0 = clk32();
                uint32_t c1 = c0 - 1;
                asm volatile("{.reg .pred p; .reg .b32 x; atom.relaxed.gpu.global.exch.b32 x, [%1], %2; setp.le.u32 p, x, %2; @p mov.u32 %0, %%clock;}"
                             : "+r"(c1) : "l"(pp + page * 4096), "r"(i) : "memory");
                t = min(t, c1 - c0);
            }
            asm volatile("st.relaxed.gpu.global.v4.b32 [%0], {%1,%1,%1,%1}; st.relaxed.gpu.global.v4.b32 [%0 + 16], {%1,%1,%1,%1};"
                         :: "l"(g_near + blockIdx.x * 16 + page * 8), "r"(ep << 12 | t) : "memory");
        }
        __syncwarp();
    } else {
        int d = 0;
#pragma unroll 1
        for (int c = 0; c < SPIN_LIM; c++) {
            uint32_t bad = 0;
            d = 0;
#pragma unroll
            for (int i = 0; i < 6; i++) { const uint32_t a = ld_relaxed(g_near + ln * 48 + i * 8); bad |= a ^ ep << 12; d += i & 1 ? -(int)a : (int)a; }
            if (__all_sync(0xffffffffu, bad < 4096)) break;
            __nanosleep(100);
        }
        const uint32_t bm = __ballot_sync(0xffffffffu, d > 0), cl = blockIdx.x / 3;
        const uint32_t side = bm >> cl & 1;
        const int n1 = 3 * __popc(bm), r1 = 3 * __popc(bm & ((1u << cl) - 1));
        const int rk = side ? r1 + blockIdx.x % 3 : blockIdx.x - r1, no = side ? 96 - n1 : n1;
        const uint32_t next = side << 8 | (rk < 40 ? 2 * rk + side : min(2 * (no + rk - 40) + (side ^ 1), 95));
        set_role(sb, next);
    }
}

__host__ __device__ constexpr int out_ord(int n) {
    return n < 8 ? n : n < 8 + LEAD ? 2 * (n - 4) : n >= 24 - LEAD ? 2 * (n - 12) + 1 : (n - LEAD) & 1 ? n - LEAD : n + LEAD;
}
__device__ __forceinline__ void share_o(uint32_t sb, uint32_t rank, uint32_t src, uint32_t t) {
#pragma unroll
    for (uint32_t p = 1; p < 3; p++) {
        const uint32_t pb = mapa(sb, (rank + p) % 3);
        asm volatile("{.reg .pred p; elect.sync _|p, 0xffffffff;\n"
                     "@p cp.async.bulk.shared::cluster.shared::cta.mbarrier::complete_tx::bytes [%0], [%1], 4096, [%2];}"
                     :: "r"(pb + OFF_OXG + t * 8192 + (2 - p) * 4096), "r"(sb + src), "r"(pb + MB_F + 8 * t) : "memory");
    }
}

#define LANE_REGS const uint32_t l16 = __shfl_sync(0xffffffffu, sb + (tid & 31) * 16, tid & 31); const int lane = (l16 - sb) >> 4

__global__ void __cluster_dims__(3, 1, 1) __launch_bounds__(384, 1)
chain_kernel(const __grid_constant__ CUtensorMap tmXA, const __grid_constant__ CUtensorMap tmXB, const __grid_constant__ CUtensorMap tmWq, const __grid_constant__ CUtensorMap tmWk,
             const __grid_constant__ CUtensorMap tmWv, const __grid_constant__ CUtensorMap tmWo,
             const __grid_constant__ CUtensorMap tmOx, const bf16* __restrict__ mem0, const bf16* xb,
             const char* win,
             bf16* out)
{
    extern __shared__ __align__(1024) uint8_t smem[];
    const uint32_t sb = smem_u32(smem);
    const int tid = threadIdx.x;
    const int warp = __shfl_sync(0xffffffffu, tid >> 5, 0);
    uint32_t rank; asm("mov.u32 %0, %%cluster_ctarank;" : "=r"(rank));
    const int head = blockIdx.x / 3;
    const char* pp = win + 0x44000 + (blockIdx.x & 63) * 64 + (blockIdx.x >> 6) * 0x100000;
    if (warp >= 10 && (tid & 31) < 8) st_pkt4(pp + (warp & 1) * 4096 + (tid & 7) * 4, 0);
    const uint32_t ep0 = ld_relaxed(&g_epoch);
    if (tid >= 160 && tid < 240) asm volatile("prefetch.global.L2 [%0];" :: "l"(mem0 + (tid - 160) * 64));

    if (tid == 256) {
        mbar_init(sb + MB_S, 5); mbar_init(sb + MB_SX, 1); mbar_init(sb + MB_O, 1); mbar_init(sb + MB_WO, 1);
        for (int i = 0; i < 4; i++) { mbar_init(sb + MB_M + 8 * i, 1); mbar_init(sb + MB_M2 + 8 * i, 1); }
        mbar_init(sb + MB_XA, 2); mbar_init(sb + MB_XB, 1); mbar_init(sb + MB_EM, 4); mbar_init(sb + MB_EA, 8);
        for (int i = 0; i < 5; i++) { mbar_init(sb + MB_F + 8 * i, 1); mbar_init(sb + MB_E + 8 * i, 8); }
        asm volatile("fence.mbarrier_init.release.cluster;" ::: "memory");
        asm volatile("fence.proxy.async.shared::cta;" ::: "memory");
        for (int i = 0; i < PWIN; i++) {
            mbar_expect(sb + MB_F + 8 * i, 32768);
            tma2d(sb + OFF_WV + i * 16384, &tmWq, head * DH + rank * 64, i * 128, sb + MB_F + 8 * i);
            tma2d(sb + OFF_WO + i * 16384, &tmWk, head * DH + rank * 64, i * 128, sb + MB_F + 8 * i);
        }
        mbar_expect(sb + MB_XA, NX * 4096); mbar_expect(sb + MB_XA, 8192); mbar_expect(sb + MB_XB, 4096);
        asm volatile("cp.async.bulk.tensor.3d.shared::cluster.global.mbarrier::complete_tx::bytes [%0], [%1, {0, 0, 3}], [%2];"
                     :: "r"(sb + OFF_XR), "l"(&tmXA), "r"(sb + MB_XA) : "memory");
        for (int i = 0; i < 3; i++)
            asm volatile("cp.async.bulk.tensor.3d.shared::cluster.global.mbarrier::complete_tx::bytes [%0], [%1, {0, 0, %3}], [%2];"
                         :: "r"(sb + OFF_MEMT + i * 4096), "l"(&tmXB), "r"(sb + (i < 2 ? MB_XA : MB_XB)), "r"(i) : "memory");
        mbar_expect(sb + MB_WO, 86016);
    }
    asm volatile("griddepcontrol.launch_dependents;" ::: "memory");
    __syncthreads();
    asm volatile("barrier.cluster.arrive.release.aligned;" ::: "memory");

    if (warp < 8) {
        asm volatile("setmaxnreg.inc.sync.aligned.u32 224;");
        LANE_REGS;
        const int w4 = warp & 3;
        const uint32_t st0 = __shfl_sync(0xffffffffu, sb + (warp >> 2) * 8192 + ((lane & 7) + ((lane >> 4) << 3)) * 128 +
                                                      (((2 * w4 + ((lane >> 3) & 1)) ^ (lane & 7)) << 4), lane);
        const uint32_t st_addr = st0 + OFF_QA;
        const uint32_t xr_lo = (((sb + OFF_XR) & 0x3FFFF) >> 4) | (1u << 16);
        const uint32_t p1 = mapa(sb, (rank + 1) % 3), p2 = mapa(sb, (rank + 2) % 3), p1s = p1 - sb + OFF_SP, p2s = p2 - sb + OFF_SP + 1280;
        const uint32_t box = rank * 7 + warp;
        const bool act = warp < 7 && box < 20;
        const uint32_t gp = XCH_PART + box * 0x4000 + head * 128;
        const int wg = __reduce_max_sync(0xffffffffu, (unsigned)tid >> 7);
        const uint32_t vo = __reduce_max_sync(0xffffffffu, ((unsigned)tid >> 7) * 32768);
        const uint32_t mo = __reduce_max_sync(0xffffffffu, ((unsigned)tid >> 7) * 5120);
        const uint32_t xa_lo = xr_lo + wg * 5 * 256, xb_lo = xr_lo + xblk(0) / 16 + wg * (2 * 256 - xblk(0) / 16);
        uint32_t wa[80], wb[80];
        {
            const uint32_t src = st_addr - OFF_QA + wg * (40960 - 8192);
            if (wg) { arrive_e(sb + MB_E); arrive_e(sb + MB_E + 8); } else { arrive_e(sb + MB_E + 24); arrive_e(sb + MB_E + 32); }
#pragma unroll
            for (int k = 0; k < 20; k++) {
                if (k % 4 == 0) mbar_wait(sb + MB_F + ((wg * 20 + k) >> 3) * 8, 0);
                ldsm4t(src + wg * OFF_WO + k * 2048, wa[4 * k], wa[4 * k + 1], wa[4 * k + 2], wa[4 * k + 3]);
                ldsm4t(src + (wg ^ 1) * OFF_WO + k * 2048, wb[4 * k], wb[4 * k + 1], wb[4 * k + 2], wb[4 * k + 3]);
                if (k % 4 == 3 && (k == 19 || (k & 4) >> 2 != wg)) arrive_e(sb + MB_E + ((wg * 20 + k) >> 3) * 8);
            }
        }
        asm volatile("barrier.cluster.wait.acquire.aligned;" ::: "memory");
        mbar_wait(sb + MB_XA, 0);

        for (int s = 0; ; s++) {
            uint32_t lb, b[10][4], v[20][4];
            auto ldv = [&](int n) { ldsm4t(st0 + vo + (OFF_WV + n * 2048), v[n][0], v[n][1], v[n][2], v[n][3]); };
            auto ldb = [&](int j) { ldsm4t(lb + mo + (OFF_MEMT + j * 512), b[j][0], b[j][1], b[j][2], b[j][3]); };
#pragma unroll
            for (int n = 0; n < NV0; n++) ldv(n);
            if (s > 0) bar_sync(BAR_WO, 384);
            {
                float pa[16], acc[16];
#pragma unroll
                for (int i = 0; i < 16; i++) pa[i] = acc[i] = 0.f;
                static_for<0, 10>([&](auto H) {
                    constexpr int h = H.value, kb = bulk_ord(h) & 7, own = bulk_ord(h) >> 3;
                    if constexpr (h == bulk_pos(0)) { if (!wg) mbar_wait(sb + MB_XB, s & 1); }
                    if constexpr (h == PW0 && h == bulk_pos(3) + 1) { if (!wg) { wg_wait<0>(); arrive_e(sb + MB_EM); } }
                    if constexpr (h == PW0 || h == PW1) { if (s >= NVC && (PW0 == PW1 || (h == PW0 ? !wg : wg))) { bar_sync(BAR_PUB, 288); } }
                    if (h == 0 || h == bulk_pos(3) + 1 + (PW0 != bulk_pos(3) + 1) || h == bulk_pos(4) + 2 || h == bulk_pos(0)) wg_fence();
                    static_for<0, 4>([&](auto K4) {
                        constexpr int k4 = K4.value, r = 16 * kb + 4 * k4;
                        const uint32_t* w = own ? wa : wb;
                        wgmma_rs32<(kb < 3 ? kb : kb - 3) * 256 + k4 * 2, k4 != 0 || h != bulk_pos(1 + own)>(own ? acc : pa, w[r], w[r + 1], w[r + 2], w[r + 3], kb < 3 ? xb_lo : xa_lo);
                    });
                    wg_commit();
                    if constexpr (h == HV) {
#pragma unroll
                        for (int n = NV0; n < NVE; n++) ldv(n);
                    }
                    if constexpr (h != PW0 && h == bulk_pos(3) + 1) { if (!wg) { wg_wait<1>(); arrive_e(sb + MB_EM); } }
                    if constexpr (h == bulk_pos(4) + 1) {
                        const uint32_t st_oth = keep((((st0 ^ opq0<8>(s)) - sb) ^ 8192) + sb) + OFF_QA;
                        wg_wait<1>();
                        stsm4t(st_oth + 1024, pack2(pa[0], pa[1]), pack2(pa[2], pa[3]), pack2(pa[4], pa[5]), pack2(pa[6], pa[7]));
                        stsm4t(st_oth + 3072, pack2(pa[8], pa[9]), pack2(pa[10], pa[11]), pack2(pa[12], pa[13]), pack2(pa[14], pa[15]));
                    }
                });
                if (s == 0) {
                    if (warp == 2) pick_role(sb, true, 0, pp, lds1(sb + OFF_EP));
#pragma unroll 1
                    for (int i = warp >> 1 & 2; i < (warp >> 1 & 2) + 3; i++) { mbar_wait_long(sb + MB_E + 8 * i, 0); mbar_wait_long(sb + MB_F + 8 * i, 1); }
#pragma unroll
                    for (int n = 0; n < NVE; n++) ldv(n);
                }
                bar_sync(BAR_QK, 256);
                uint32_t u[8];
                ldsm4t(st_addr + 1024, u[0], u[1], u[2], u[3]);
                ldsm4t(st_addr + 3072, u[4], u[5], u[6], u[7]);
#pragma unroll
                for (int n = NVE; n < NVP; n++) ldv(n);
                lb = keep(sb + mem_row(laneid() + opq0<10>(s)));
                wg_wait<0>();
                arrive_e(sb + MB_EA);
#pragma unroll
                for (int i = 0; i < 8; i++) u[i] = badd2(u[i], pack2(acc[2 * i], acc[2 * i + 1]));
                stsm4t(st_addr + 1024, u[0], u[1], u[2], u[3]);
                stsm4t(st_addr + 3072, u[4], u[5], u[6], u[7]);
                if (RB && wg) bar_arrive(BAR_R1, 288);
            }
            uint32_t lo = 0, so = 0, a[16], kb[8], k1[8];
            const uint32_t r1 = s == NSEG - 1 ? OFF_R1L : OFF_R1;
            float cv[4] = {0, 0, 0, 0};
            {
                float ca[4] = {0, 0, 0, 0}, cb[4] = {0, 0, 0, 0};
                uint32_t sq = 0, ln = 0, lq = 0, lk = 0;
                blk(warp);
                if (wg) bar_sync(BAR_MEM + 2, 160); else bar_sync(BAR_MEM, 160);
                int nb = 0, nv = NVP;
                for (; nb < BD; nb++) ldb(nb);
#pragma unroll
                for (int j = 0; j < 10; j++) {
                    if (2 * j == BN) { if (wg) bar_sync(BAR_MEM + 3, 160); else bar_sync(BAR_MEM + 1, 160); }
                    for (; nb <= j + BD && nb < (2 * j >= BN ? 10 : 5); nb++) ldb(nb);
                    if (j == KJ) {
                        if (!RB) bar_sync(BAR_R1, 288); else if (wg) bar_sync(BAR_PM, 160); else bar_sync(BAR_R1, 288);
#pragma unroll
                        for (int i = 0; i < 4; i++) { kb[i] = b[KJ - 2][i]; kb[4 + i] = b[KJ - 1][i]; }
                        ldsm4_if((uint32_t)(warp - 1) < 4, OFF_KA + lo, kb[0], kb[1], kb[2], kb[3]);
                        ldsm4_if((uint32_t)(warp - 1) < 4, OFF_KA + (lo ^ 64), kb[4], kb[5], kb[6], kb[7]);
                    }
                    blk(warp);
#pragma unroll
                    for (int i = 0; i < 2; i++) {
                        const int n = 2 * j + i;
                        if (i && n == BN) {
                            if (wg) bar_sync(BAR_MEM + 3, 160); else bar_sync(BAR_MEM + 1, 160);
                            for (; nb <= j + BD; nb++) ldb(nb);
                            blk(warp);
                        }
                        mma16(cb, wb[4 * n], wb[4 * n + 1], wb[4 * n + 2], wb[4 * n + 3], b[j][2 * i], b[j][2 * i + 1]);
                        mma16(ca, wa[4 * n], wa[4 * n + 1], wa[4 * n + 2], wa[4 * n + 3], b[j][2 * i], b[j][2 * i + 1]);
                        mma16(cv, v[n][0], v[n][1], v[n][2], v[n][3], b[j][2 * i], b[j][2 * i + 1]);
                        if (n >= NVP - NVR && nv < 20) ldv(nv++);
                    }
                    if (j == AJ) { const uint32_t o = (st0 ^ opq0<9>(s)) - sb; ln = keep((o >> 7 & 7) | ((o ^ o >> 3) >> 1 & 8) | (o >> 6 & 16)); }
                    if (j == AJ + 1) lo = keep(sb + (ln & 7) * 128 + (((ln >> 3) ^ (ln & 7)) << 4) + warp * 1024);
                    if (j == AJ + 2) {
                        lk = keep(sb + ln * 16);
                        sq = keep((lk & ~256u) + (warp & 3) * 256 + selu((ln >> 4) == warp >> 2, r1 + (warp >> 2) * 1024, OFF_KA - (warp >> 2) * 8192));
                    }
                    if (j == AJ + 3) so = keep(sb + warp * 256 + ((ln * 8) ^ (warp & 3) * 32));
                    if (j == AJ + 4) lq = keep(sb + r1 + (ln & 8) * 128 + (ln >> 4) * 128 + (ln & 7) * 16);
                    if (j == AJ + 5) {
#pragma unroll
                        for (int i = 0; i < 8; i++) k1[i] = opq0<11>(s);
                    }
                }
                a[0] = pack2(ca[0], ca[1]); a[1] = pack2(ca[2], ca[3]); a[2] = pack2(cb[0], cb[1]); a[3] = pack2(cb[2], cb[3]);
                stsm4t(sq, a[0], a[1], a[2], a[3]);
                sts2(so + r1 + 2048, pack2(cv[0], cv[1]), pack2(cv[2], cv[3]));
                bar_sync(BAR_QM, 256);
#pragma unroll
                for (int i = 0; i < 4; i++) { a[4 + i] = __float_as_uint(ca[i]); a[8 + i] = __float_as_uint(cb[i]); a[12 + i] = b[9][i]; }
                ldsm4_if(warp < 5, lq, a[0], a[1], a[2], a[3]);
                ldsm4_if(warp == 0, lk + OFF_KA, kb[0], kb[1], kb[2], kb[3]);
                ldsm4_if(warp < 5, lq + 256, a[4], a[5], a[6], a[7]);
                ldsm4_if(warp == 0, lk + OFF_QA, k1[0], k1[1], k1[2], k1[3]);
                ldsm4_if(warp < 5, lq + 512, a[8], a[9], a[10], a[11]);
                ldsm4_if(warp == 0, lk + OFF_KA + 512, kb[4], kb[5], kb[6], kb[7]);
                ldsm4_if(warp < 5, lq + 768, a[12], a[13], a[14], a[15]);
                ldsm4_if(warp == 0, lk + OFF_QA + 512, k1[4], k1[5], k1[6], k1[7]);
            }
            if (__builtin_expect(warp < 5, 1)) {
                const uint32_t r1a = keep(p1s + so), r2a = keep(p2s + so), m1 = keep(p1 + MB_S), m2 = keep(p2 + MB_S);
                blk(warp);
#pragma unroll
                for (int i = 0; i < 8; i++) kb[i] = badd2(kb[i], k1[i]);
                float d[4][4];
#pragma unroll
                for (int i = 0; i < 4; i++) {
                    d[i][0] = d[i][1] = d[i][2] = d[i][3] = 0.f;
                    mma16(d[i], a[4 * i], a[4 * i + 1], a[4 * i + 2], a[4 * i + 3], kb[2 * i], kb[2 * i + 1]);
                }
                const uint32_t x = __float_as_uint((((d[0][0] + d[0][2]) + (d[1][0] + d[1][2])) + (d[2][0] + d[2][2])) + (d[3][0] + d[3][2]));
                const uint32_t y = __float_as_uint((((d[0][1] + d[0][3]) + (d[1][1] + d[1][3])) + (d[2][1] + d[2][3])) + (d[3][1] + d[3][3]));
                st_async2(r1a, x, y, m1);
                st_async2(r2a, x, y, m2);
                sts2(so + OFF_SM, x, y);
                __syncwarp();
                expect_e(sb + MB_S, 512);
                if (warp == 0) { stsm4(OFF_KA + lo, kb[0], kb[1], kb[2], kb[3]); stsm4(OFF_KA + (lo ^ 64), kb[4], kb[5], kb[6], kb[7]); }
                bar_arrive(BAR_S, 288); bar_arrive(BAR_O2, 256);
            } else {
                if (warp == 7 && s < NSEG - 1) {
                    pause<SD>();
                    const uint32_t now = gtime() & ~31u, ln = laneid(), sq = (s - lds1(sb + OFF_EP)) & 3;
                    if (ln < 4) st_pkt4(win + 0x44000 + xch_copy(1 + (ln & 1)) + (ln >> 1) * 4096 + blockIdx.x * 4, now | sq);
                    __syncwarp();
                }
                if (warp == 6 && s < NSEG - 1) {
                    asm volatile("fence.proxy.async.shared::cta;" ::: "memory");
                    expect_e(sb + MB_XA, 8192);
                    tma3d_e(sb + OFF_MEMT, &tmXB, (s + 1) * 32, 0, sb + MB_XA);
                    tma3d_e(sb + OFF_MEMT + 4096, &tmXB, (s + 1) * 32, 1, sb + MB_XA);
                }
                bar_sync(BAR_O2, 256);
            }
            if (s == NSEG - 1) break;
            const uint32_t ln = laneid();
            auto softmax = [&](auto&& more) {
                const uint32_t pb = warp * 32 + (ln & 3) * 8, kt = min(ln >> 2, 4u);
                const uint32_t pw = keep(sb + OFF_PM + pb + selu(ln < 4, 0, pb + 256 + (~kt & 1) * 8 + ((kt + 1) & 4)));
                const uint32_t sr = keep(sb + OFF_SM + kt * 256 + (pb ^ (kt & 3) * 32));
                mbar_wait(sb + MB_S, s & 1);
                const float2 u = lds2f(sr), t = lds2f(sr + (OFF_SP - OFF_SM)), w = lds2f(sr + (OFF_SP + 1280 - OFF_SM));
                more();
                float x = u.x + t.x + w.x, y = u.y + t.y + w.y;
                const int m = __float_as_int(fmaxf(x, y)), hi = __reduce_max_sync(0xffffffffu, m), lw = __reduce_min_sync(0xffffffffu, m);
                const float mx = __int_as_float(hi >= 0 ? hi : lw) * -SCL_B;
                x = ex2(fmaf(x, SCL_B, mx)); y = ex2(fmaf(y, SCL_B, mx));
                sts1(pw, pack2(x, y));
                bar_sync(BAR_PM, 384);
            };
            if (act) {
                const uint32_t wo0 = keep(sb + OFF_WO + warp * 4096 + ((ln & 7) + ((ln >> 4) << 3)) * 64 + ((((ln >> 3) & 1) ^ ((ln >> 1) & 3)) << 4)), wo1 = keep(wo0 ^ 32);
                const uint32_t tag = (__shfl_sync(0xffffffffu, lds1(sb + OFF_EP), 0) ^ s) & 1;
                uint32_t f[24][4];
                auto ld = [&](int n) { ldsm4t((out_ord(n) & 1 ? wo1 : wo0) + (out_ord(n) >> 3) * 28672 + (out_ord(n) >> 1 & 3) * 1024, f[n][0], f[n][1], f[n][2], f[n][3]); };
#pragma unroll
                for (int n = 0; n < NPE; n++) ld(n);
                softmax([&]() {
#pragma unroll
                    for (int n = NPE; n < NPM; n++) ld(n);
                });
                if (s == 0) {
                    mbar_wait_long(sb + MB_WO, 0);
#pragma unroll
                    for (int n = 0; n < NPM; n++) ld(n);
                }
#pragma unroll
                for (int n = NPM; n < NPF; n++) ld(n);
                const uint32_t l8 = keep(sb + ln * 8);
                const char* dst = nullptr;
                blk(warp);
                bar_sync(BAR_O, 384);
                float2 bb[12];
                auto ldo = [&](int i) { bb[i] = lds2f(l8 + OFF_R1 + (i + 8) % 12 * 256); };
                float e[2][4] = {{0, 0, 0, 0}, {0, 0, 0, 0}};
                int nl = NPF, nb = 0;
#pragma unroll
                for (int n = 0; n < 24; n++) {
                    const int k = out_ord(n) >> 1, t = out_ord(n) & 1;
                    if (n == 8) { bar_sync(BAR_O2, 256); }
                    if (n == 0 || n == 8) { for (int i = 0; i < NOB; i++) ldo(nb++); blk(warp); }
                    mma16(e[t], f[n][0], f[n][1], f[n][2], f[n][3], __float_as_uint(bb[k].x), __float_as_uint(bb[k].y));
                    if (t && nb < (n < 8 ? 4 : 12)) ldo(nb++);
                    if (n > 1 && nl < 24) ld(nl++);
                    if (n == 17) { const uint32_t o = keep(l8); dst = keepp(win + (gp + ((o & 128) << 5) + (o & 127))); }
                    if (n == 23 || (LEAD && n == 24 - LEAD)) {
                        if (n < 23 || !LEAD) st_pkt8(dst, (pack2(e[0][0], e[0][1]) & ~1u) | tag, pack2(e[0][2], e[0][3]));
                        if (n == 23) st_pkt8(dst + 0x2000, (pack2(e[1][0], e[1][1]) & ~1u) | tag, pack2(e[1][2], e[1][3]));
                    }
                    if (t || out_ord(n + 1) % 2 == 0) blk(warp);
                }
            } else {
                softmax([]() { });
                if (warp != 7) { bar_arrive(BAR_O, 384); bar_arrive(BAR_O2, 256); }
                else {
                    const uint32_t now = (gtime() & ~31u) | ((s - lds1(sb + OFF_EP)) & 3);
                    const char* sp = win + (lds1(sb + OFF_SPO) + min(ln, 23u) * 16);
                    expect_e(sb + MB_XB, 4096);
                    bar_sync(BAR_O, 384);
                    asm volatile("fence.proxy.async.shared::cta;" ::: "memory");
                    uint4 sv = ld_pkt(sp);
                    tma3d_e(sb + OFF_MEMT + 8192, &tmXB, (s + 1) * 32, 2, sb + MB_XB);
                    mbar_wait(sb + MB_O, s & 1);
                    bar_arrive(BAR_O2, 256);
                    blk(s);
                    int d;
                    for (int c = 0; ; c++) {
                        const int d0 = sv.x - now, d1 = sv.y - now, d2 = sv.z - now, d3 = sv.w - now;
                        d = max(max(d0, d1), max(d2, d3));
                        if (!__any_sync(0xffffffffu, (d0 | d1 | d2 | d3) & 2) || c == 512) break;
                        sv = ld_pkt(sp);
                    }
                    sts1(sb + OFF_T, (now + min(__reduce_max_sync(0xffffffffu, d), 8192)) & ~31u);
                    bar_arrive(BAR_G, 64);
                    mbar_wait(sb + MB_XA, (s + 1) & 1);
                }
            }
        }
        asm volatile("setmaxnreg.dec.sync.aligned.u32 168;");
        uint32_t f[24][4];
        const uint32_t lnt = laneid(), ep = lds1(sb + OFF_EP);
        {
            const uint32_t wo0 = sb + OFF_WO + warp * 4096 + ((lnt & 7) + ((lnt >> 4) << 3)) * 64 + ((((lnt >> 3) & 1) ^ ((lnt >> 1) & 3)) << 4);
#pragma unroll
            for (int n = 0; n < 24; n++) ldsm4t((wo0 ^ (n / 12) * 32) + (n % 12 >> 2) * 28672 + (n & 3) * 1024, f[n][0], f[n][1], f[n][2], f[n][3]);
        }
        char* tp = reinterpret_cast<char*>(g_tail) + head * 40960 + box * 2048 + lnt * 16;
#pragma unroll 1
        for (int t = 0; t < 2; t++) {
            const uint32_t b0 = (((sb + (t ? OFF_OXL : OFF_OX)) & 0x3FFFF) >> 4) | (1u << 16), b1 = (((sb + OFF_OXG + t * 8192) & 0x3FFFF) >> 4) | (1u << 16);
            float acc[2][16];
#pragma unroll
            for (int i = 0; i < 16; i++) acc[0][i] = acc[1][i] = 0.f;
            auto st = [&](int i) {
                const float* a = acc[i];
                st_pkt(tp + i * 1024, make_uint4((pack2(a[0], a[1]) & ~1u) | (ep & 1), pack2(a[2], a[3]), pack2(a[4], a[5]), pack2(a[6], a[7])));
                st_pkt(tp + i * 1024 + 512, make_uint4((pack2(a[8], a[9]) & ~1u) | (ep & 1), pack2(a[10], a[11]), pack2(a[12], a[13]), pack2(a[14], a[15])));
            };
            if (t) bar_sync(BAR_WO, 384);
            wg_fence();
            static_for<0, 8>([&](auto N) {
                constexpr int i = N.value >> 2, k = N.value & 3;
                wgmma_rs32<k * 2, k != 0>(acc[i], f[12 * i + k][0], f[12 * i + k][1], f[12 * i + k][2], f[12 * i + k][3], b0);
            });
            wg_commit();
            mbar_wait(sb + MB_F + 8 * t, 0);
            static_for<0, 2>([&](auto I) {
                constexpr int i = I.value;
                wg_fence();
                static_for<4, 12>([&](auto K) {
                    constexpr int k = K.value;
                    wgmma_rs32<(k / 4 - 1) * 256 + (k & 3) * 2, 1>(acc[i], f[12 * i + k][0], f[12 * i + k][1], f[12 * i + k][2], f[12 * i + k][3], b1);
                });
                wg_commit();
            });
            wg_wait<1>();
            if (act) st(0);
            wg_wait<0>();
            if (act) st(1);
            if (t) bar_arrive(BAR_X, 384);
            tp += 32 * 40960;
        }
    } else {
        asm volatile("setmaxnreg.dec.sync.aligned.u32 56;");
        const int g = __reduce_max_sync(0xffffffffu, (unsigned)tid >> 5 & 3);
        if (g >= 2) pick_role(sb, false, g & 1, pp, ep0 + 1);
        const uint32_t ep = __reduce_max_sync(0xffffffffu, ep0) + 1;
        sts1(sb + OFF_EP, ep);
#pragma unroll
        for (int i = 0; i < 5; i++) {
            const unsigned short* m = reinterpret_cast<const unsigned short*>(mem0) + g * 160 + (tid & 31) + 32 * i;
            sts4(sb + (tid & 127) * 16 + (i < 4 ? OFF_SX + i * 2048 : OFF_WO + 81920),
                 make_uint4(m[0] | ((uint32_t)m[DM] << 16), m[2 * DM] | ((uint32_t)m[3 * DM] << 16),
                            m[4 * DM] | ((uint32_t)m[5 * DM] << 16), m[6 * DM] | ((uint32_t)m[7 * DM] << 16)));
        }
        asm volatile("barrier.cluster.wait.acquire.aligned;" ::: "memory");
        if (g == 0) {
            const int e0 = head * DH + rank * 64;
            for (int i = PWIN; i < 5; i++) {
                mbar_wait(sb + MB_F + 8 * (i - PWIN), 0);
                expect_e(sb + MB_F + 8 * i, 32768);
                tma2d_e(sb + OFF_WV + i * 16384, &tmWq, e0, i * 128, sb + MB_F + 8 * i);
                tma2d_e(sb + OFF_WO + i * 16384, &tmWk, e0, i * 128, sb + MB_F + 8 * i);
            }
            for (int i = 0; i < 5; i++) {
                mbar_wait(sb + MB_E + 8 * i, 0);
                if (i + 5 - PWIN < 5) mbar_wait(sb + MB_F + 8 * (i + 5 - PWIN), 0);
                expect_e(sb + MB_F + 8 * i, 16384);
                tma2d_e(sb + OFF_WV + i * 16384, &tmWv, e0, i * 128, sb + MB_F + 8 * i);
            }
        }
        uint32_t role = 0, ph = 0, tg = 0;
        uint32_t o16 = __shfl_sync(0xffffffffu, (tid & 31) * 16, tid & 31);
        auto gather = [&](int s) {
            const char* mb = win + (role >> 8 & 1) * 4096 + xch_copy((role >> 1) % NCP);
            mbar_wait(sb + MB_EM, s & 1);
            ggate(tg + G2);
            pause<F2>();
#pragma unroll
            for (int i = 0; i < 4; i++) { const int c = (i & 1) * 2 + (i >> 1); bulk_ld_e(sb + OFF_MEMT + c * 2560, mb + xch_mem(c), 2560, sb + MB_M + 8 * c); }
            bar_arrive(BAR_G, 64);
        };

        for (int s = 0; ; s++) {
            uint32_t vx[8];
            o16 += opq0<8>(s);
            const uint32_t lz = sb + o16;
            const uint4* vp = keepp(g_vx + (blockIdx.x * 64 + s) * 256 + g * 32 + (o16 >> 4));
            auto load_v = [&]() {
                const uint4 u = ld_pkt(vp), v = ld_pkt(vp + 128);
                vx[0] = u.x; vx[2] = u.y; vx[1] = u.z; vx[3] = u.w; vx[4] = v.x; vx[6] = v.y; vx[5] = v.z; vx[7] = v.w;
            };
            const char* mb = win + (role >> 8 & 1) * 4096 + xch_copy((role >> 1) % NCP);
            auto store_x = [&]() {
                if (g == 3) {
                    bar_sync(BAR_G, 64);
                    if (o16 == 0 && s < NSEG - 1) { tma_st(&tmOx, sb + OFF_OX, blockIdx.x * 64, (s - 1) * 32); asm volatile("cp.async.bulk.commit_group;" ::: "memory"); }
                    __syncwarp();
                }
            };
#pragma unroll
            for (int j = 0; j < 8; j++) vx[j] = 0;
            if (s > NVC) load_v();
            if (s >= NVC) store_x();
            if (s < NVC) {
                const uint32_t wv_lo = (((sb + OFF_WV) & 0x3FFFF) >> 4) | (64u << 16), xr_lo = (((sb + OFF_XR) & 0x3FFFF) >> 4) | (1u << 16);
                float acc[16];
#pragma unroll
                for (int i = 0; i < 16; i++) acc[i] = 0.f;
                mbar_wait(sb + MB_XA, s & 1);
                mbar_wait(sb + MB_XB, s & 1);
                static_for<0, 10>([&](auto KB) {
                    constexpr uint32_t kb = KB.value;
                    if (kb == 4) {
                        wg_wait<1>();
                        bar_sync(BAR_P, 128);
                        if (s > 0) { if (g == 1) gather(s); store_x(); }
                        else {
                            const uint32_t ln = laneid();
                            mbar_wait_long(sb + MB_EM, 0);
#pragma unroll
                            for (int i = 0; i < 5; i++)
                                sts4(sb + mem_row(ln) + OFF_MEMT + g * 2560 + 512 * i, lds4(sb + g * 512 + ln * 16 + (i < 4 ? OFF_SX + i * 2048 : OFF_WO + 81920)));
                            asm volatile("fence.proxy.async.shared::cta;" ::: "memory");
                            bar_sync(BAR_P, 128);
                            arrive_e(sb + MB_M + 8 * g);
                        }
                    }
                    if (!(kb & 1) && s == 0) {
                        mbar_wait_long(sb + MB_E + 4 * kb, 0);
                        mbar_wait_long(sb + MB_F + 4 * kb, 1);
#pragma unroll
                        for (int p = 0; p < 3; p++)
                            if (kb == (WOK >> 4 * p & 15) && g == 0) tma3d_e(sb + OFF_WO + p * 28672, &tmWo, head * DH + (rank + p) % 3 * 64, rank * 7, sb + MB_WO);
                    }
                    wg_fence();
                    static_for<0, 4>([&](auto K4) { wgmma_ss32<(kb * 4 + K4.value) * 128, xblk(kb) / 16 + K4.value * 2, (kb | K4.value) != 0>(acc, wv_lo, xr_lo); });
                    wg_commit();
                });
                wg_wait<0>();
#pragma unroll
                for (int j = 0; j < 8; j++) vx[j] = pack2(acc[2 * j], acc[2 * j + 1]);
                bar_sync(BAR_P, 128);
            }
            const uint32_t* fv = g_flagv + blockIdx.x * 64 + (s == NVC ? s : s + 1);
            uint32_t fl = ep;
            if (s == NVC || (g == 0 && s > NVC && (VFLAGS >> 1 >> s & 1))) fl = ld_relaxed(fv);
            {
                const uint32_t mt = keep(sb + OFF_MEMT + g * 2560 + o16 * 2 + (o16 >> 4 & 28)), tag = (s ^ ep ^ 1) & 1, msk = keep(s > 0);
                const int bar = keep(BAR_MEM + g);
                auto stale = [&](uint32_t m) {
                    const uint32_t w0 = lds1(mt), w1 = lds1(mt + 1024), w2 = lds1(mt + 1536);
                    return arrive_unless(tagx(w0, w1, tag) | (w2 ^ tag), m, bar, 160);
                };
                mbar_wait_long(sb + MB_M + 8 * g, s & 1);
                if (stale(msk)) {
                    for (int cnt = 0; ; cnt++) {
                        asm volatile("fence.proxy.async.shared::cta;" ::: "memory");
                        __syncwarp();
                        expect_e(sb + MB_M2 + 8 * g, 2560);
                        bulk_ld_e(sb + OFF_MEMT + g * 2560, mb + xch_mem(g), 2560, sb + MB_M2 + 8 * g);
                        mbar_wait_long(sb + MB_M2 + 8 * g, ph);
                        ph ^= 1;
                        if (!stale(cnt < WAIT_LIM)) break;
                    }
                }
            }
            if (g == 3) { asm volatile("cp.async.bulk.wait_group.read 0;" ::: "memory"); __syncwarp(); bar_arrive(BAR_R1, 288); if (RB) bar_arrive(BAR_PM, 160); }
            if (g == XG && s < NSEG - 1) {
                mbar_wait(sb + MB_EA, s & 1);
                expect_e(sb + MB_XA, NX * 4096);
                tma3d_e(sb + OFF_XR, &tmXA, (s + 1) * 32, 3, sb + MB_XA);
            }
            if (fl != ep) for (int c = 0; c < SPIN_LIM && ld_acquire(fv) != ep; c++) { }
            if (s == NVC) load_v();
            if (PFV && g == 0 && s >= NVC && s < NSEG - 1) asm volatile("prefetch.global.L2 [%0];" :: "l"(g_vx + (blockIdx.x * 64 + s + 1) * 256 + (o16 >> 1)));
            if (PFX && g == 2 && s < NSEG - 2 && blockIdx.x < 80 && o16 < 64)
                asm volatile("prefetch.global.L2 [%0];" :: "l"(reinterpret_cast<const char*>(xb) + (s + 2) * 40960 + blockIdx.x * 512 + o16 * 8));
            if (s < NSEG - 1) {
                if (g == 0) expect_e(sb + MB_O, 2048);
            } else if (g == 0) {
                expect_e(sb + MB_F, 8192); expect_e(sb + MB_F + 8, 8192);
            }
            if (g == 1) expect_e(sb + MB_SX, 5120);
            auto progress = [&]() {
                if (g == 3 && (PROG >> s & 1)) {
                    if (o16 == 0) {
                        asm volatile("cp.async.bulk.wait_group 0;" ::: "memory");
                        st_pkt4(g_prog + blockIdx.x + (keep(s) >> 8), ep * 128 + s);
                    }
                    __syncwarp();
                }
            };
            progress();
            const uint32_t q1 = keep(mapa(sb, (rank + 1) % 3) - sb), q2 = keep(mapa(sb, (rank + 2) % 3) - sb);
            uint32_t own[5], vm0, vm1;
            {
                const uint32_t qa_lo = (((sb + OFF_QA + 1024) & 0x3FFFF) >> 4) | (1u << 16), ka_lo = (((sb + OFF_KA) & 0x3FFFF) >> 4) | (1u << 16);
                const uint32_t va = keep(sb + ((o16 >> 1) ^ g * 32) + g * 256 + (s == NSEG - 1 ? OFF_R1L : OFF_R1) + 2048);
                float d[20];
#pragma unroll
                for (int j = 0; j < 20; j++) d[j] = 0.f;
                bar_sync(BAR_S, 288);
                const float2 u = lds2f(va), v = lds2f(va + 1024);
                role = __shfl_sync(0xffffffffu, lds1(sb + OFF_ROLE), 0);
                asm volatile("fence.proxy.async.shared::cta;" ::: "memory");
                wg_fence();
                static_for<0, 4>([&](auto K4) { wgmma_ss40<K4.value * 2, K4.value != 0>(d, qa_lo, ka_lo); });
                wg_commit();
                if (s < NSEG - 1) expect_e(sb + MB_M + 8 * g, 2560);
                vm0 = badd2(__float_as_uint(u.x), __float_as_uint(v.x)); vm1 = badd2(__float_as_uint(u.y), __float_as_uint(v.y));
                const uint32_t xo = lz + OFF_SX + g * 640, mo = sb + OFF_SX + g * 640 + 512 + (o16 >> 2);
                const int lim = 8 + 8 * g + (o16 >> 6) - ((o16 >> 3) & 6);
                wg_wait<0>();
#pragma unroll
                for (int j = 0; j < 5; j++) own[j] = pack2(8 * j > lim ? -INFINITY : d[4 * j], 8 * j + 1 > lim ? -INFINITY : d[4 * j + 1]);
                mbar_wait(sb + MB_S, s & 1);
                st_async4(q1 + xo + 2560, own[0], own[1], own[2], own[3], q1 + sb + MB_SX); st_async4(q2 + xo, own[0], own[1], own[2], own[3], q2 + sb + MB_SX);
                st_async1(q1 + mo + 2560, own[4], q1 + sb + MB_SX);                         st_async1(q2 + mo, own[4], q2 + sb + MB_SX);
            }
            if (s < NSEG - 1) {
                const uint32_t pm = keep(sb + OFF_PM + (o16 >> 1)), oo = keep(pm + (OFF_R1 - OFF_PM) + g * 256);
                blk(s);
                bar_sync(BAR_PM, 384);
                const uint4 qq = lds4(lz + OFF_PM + 256);
                const uint32_t p0 = lds1(pm);
                float oa[2][4] = {{0, 0, 0, 0}, {0, 0, 0, 0}}, ob[2][4] = {{0, 0, 0, 0}, {0, 0, 0, 0}}, os[4] = {0, 0, 0, 0};
                mma16(os, qq.x, qq.y, qq.z, qq.w, 0x3f803f80, 0x3f803f80);
                mma16(oa[0], qq.x, qq.y, qq.z, qq.w, vx[0], vx[2]);
                mma16(oa[1], qq.x, qq.y, qq.z, qq.w, vx[1], vx[3]);
                mma16(ob[0], qq.x, qq.y, qq.z, qq.w, vx[4], vx[6]);
                mma8(os, p0, 0, 0x3f803f80);
                mma16(ob[1], qq.x, qq.y, qq.z, qq.w, vx[5], vx[7]);
                mma8(oa[0], p0, 0, vm0);
                mma8(oa[1], p0, 0, vm1);
                const float inv = rcpf(os[0] + os[2]);
                const uint32_t o0 = pack2((oa[0][0] + ob[0][2]) * inv, (oa[0][1] + ob[0][3]) * inv), o1 = pack2((oa[1][0] + ob[1][2]) * inv, (oa[1][1] + ob[1][3]) * inv);
                st_async2(q1 + oo + 1024, o0, o1, q1 + sb + MB_O);
                st_async2(q2 + oo, o0, o1, q2 + sb + MB_O);
                sts2(oo + 2048, o0, o1);
                bar_arrive(BAR_O, 384);
            } else if (g == 1) {
                share_o(sb, rank, OFF_OX, 0);
            }
            {
                float sc[10], mx;
                const uint32_t xo = lz + OFF_SX + g * 640, pa = sb + OFF_SX + g * 640 + (o16 >> 2);
                mbar_wait(sb + MB_SX, s & 1);
                const uint4 u = lds4(xo), v = lds4(xo + 2560);
                const uint32_t um = lds1(pa + 512), vm = lds1(pa + 512 + 2560);
#define SSUM(k, a, b, c) sc[k] = (bf_lo(a) + bf_lo(b)) + bf_lo(c); sc[k + 1] = (bf_hi(a) + bf_hi(b)) + bf_hi(c);
                SSUM(0, own[0], u.x, v.x) SSUM(2, own[1], u.y, v.y) SSUM(4, own[2], u.z, v.z) SSUM(6, own[3], u.w, v.w) SSUM(8, own[4], um, vm)
#undef SSUM
                mx = fmaxf(fmaxf(fmaxf(sc[2], sc[3]), fmaxf(sc[4], sc[5])), fmaxf(fmaxf(fmaxf(sc[6], sc[7]), fmaxf(sc[8], sc[9])), fmaxf(sc[0], sc[1])));
                mx = fmaxf(fmaxf(mx, __shfl_xor_sync(0xffffffffu, mx, 1)), fmaxf(__shfl_xor_sync(0xffffffffu, mx, 2), __shfl_xor_sync(0xffffffffu, mx, 3)));
                mx *= -SCL_B;
                float sum = 0.f;
#pragma unroll
                for (int j = 0; j < 10; j++) { sc[j] = ex2(fmaf(sc[j], SCL_B, mx)); sum += sc[j]; }
                sum = (sum + __shfl_xor_sync(0xffffffffu, sum, 1)) + (__shfl_xor_sync(0xffffffffu, sum, 2) + __shfl_xor_sync(0xffffffffu, sum, 3));
                const float inv = rcpf(sum);
#pragma unroll
                for (int j = 0; j < 5; j++) sts1(pa + j * 128, pack2(sc[2 * j] * inv, sc[2 * j + 1] * inv));
                asm volatile("fence.proxy.async.shared::cta;" ::: "memory");
            }
            float acc[16];
            {
                const uint32_t px_lo = (((sb + OFF_SX) & 0x3FFFF) >> 4) | (8u << 16);
                uint32_t a[12];
                const uint32_t z = opq0<8>(s);
#pragma unroll
                for (int i = 0; i < 12; i++) asm volatile("xor.b32 %0, %1, %2;" : "=r"(a[i]) : "r"(i < 8 ? vx[i & 7] : i == 8 ? vm0 : i == 9 ? vm1 : 0u), "r"(z));
#pragma unroll
                for (int i = 0; i < 16; i++) acc[i] = 0.f;
                if (g == 1 && s < NSEG - 1) { bar_sync(BAR_G, 64); tg = lds1(sb + OFF_T); }
                if (s < NSEG - 1) bar_sync(BAR_WO, 384); else bar_sync(BAR_P, 128);
                wg_fence();
                wgmma_rs32n<0, 0>(acc, a[8], a[9], a[10], a[11], px_lo);
                wgmma_rs32n<8, 1>(acc, a[0], a[1], a[2], a[3], px_lo);
                wgmma_rs32n<24, 1>(acc, a[4], a[5], a[6], a[7], px_lo);
                wg_commit();
            }
            o16 += opq0<9>(s);
            const uint32_t ln = o16 >> 4;
            const uint32_t sa = keep(sb + (s == NSEG - 1 ? OFF_OXL : OFF_OX) + ((ln & 7) + ((ln >> 4) << 3)) * 128 + (((2 * g + ((ln >> 3) & 1)) ^ (ln & 7)) << 4));
            auto store_o = [&]() {
                wg_wait<0>();
                stsm4t(sa, pack2v(acc[0], acc[1]), pack2v(acc[2], acc[3]), pack2v(acc[4], acc[5]), pack2v(acc[6], acc[7]));
                stsm4t(sa + 2048, pack2v(acc[8], acc[9]), pack2v(acc[10], acc[11]), pack2v(acc[12], acc[13]), pack2v(acc[14], acc[15]));
            };
            if ((role & 255) < 80 && s < NSEG - 1) {
                const char* rp = keepp(win + (XCH_PART + (role & 255) * 4096 + g * 1024 + (o16 >> 1)));
                const char* wp = keepp(win + ((role >> 9 << 7) + (((o16 >> 4 ^ role) & 1) * 4 + (o16 >> 7)) * 16 + (o16 >> 3 & 12)));
                const uint32_t tag = (s ^ ep) & 1, rb = keep(sb + (o16 >> 1));
                uint32_t x[4], y[4];
                auto load = [&]() { static_for<0, 4>([&](auto I) { ld_pkt8<I.value * 256>(x[I.value], y[I.value], rp); }); };
                auto sum8 = [&](uint32_t m) {
                    sts4(sb + o16 + OFF_RED + g * 512,
                         make_uint4(__float_as_uint(((bf_lo(x[0]) + bf_lo(x[1])) + bf_lo(x[2])) + bf_lo(x[3])), __float_as_uint(((bf_hi(x[0]) + bf_hi(x[1])) + bf_hi(x[2])) + bf_hi(x[3])),
                                    __float_as_uint(((bf_lo(y[0]) + bf_lo(y[1])) + bf_lo(y[2])) + bf_lo(y[3])), __float_as_uint(((bf_hi(y[0]) + bf_hi(y[1])) + bf_hi(y[2])) + bf_hi(y[3]))));
                    return sync_unless(tagx(x[0], x[1], tag), tagx(x[2], x[3], tag), m, BAR_R, 128);
                };
                auto again = [&]() { for (int cnt = 0; ; cnt++) { load(); if (!sum8(cnt < WAIT_LIM)) break; } };
                if (g == 0) {
                    bar_sync(BAR_R, 128);
                    load();
                    store_o();
                    const bool st = sum8(1);
                    float2 r[8];
#pragma unroll
                    for (int i = 0; i < 8; i++) r[i] = lds2f(rb + OFF_RED + i * 256);
                    if (REL == 1 && s >= NVC - 1) bar_arrive(BAR_PUB, 288);
                    if (st) {
                        again();
#pragma unroll
                        for (int i = 0; i < 8; i++) r[i] = lds2f(rb + OFF_RED + i * 256);
                    }
                    const float k0 = ((r[0].x + r[1].x) + (r[2].x + r[3].x)) + ((r[4].x + r[5].x) + (r[6].x + r[7].x));
                    const float k1 = ((r[0].y + r[1].y) + (r[2].y + r[3].y)) + ((r[4].y + r[5].y) + (r[6].y + r[7].y));
                    const uint32_t kb = __float_as_uint(k0);
                    const uint32_t pk = __byte_perm(kb + ((kb ^ tag << 16) & 0x10000), pack2(0.f, k1), 0x7632);
#pragma unroll
                    for (int i = 0; i < 2 * NCP; i++) st_pkt4(wp + xch_copy(i >> 1) + (i & 1) * 4096, pk);
                    if (REL == 2 && s >= NVC - 1) bar_arrive(BAR_PUB, 288);
                } else {
                    if (g == 1) { ggate(tg + G1); pause<F1>(); }
                    bar_sync(BAR_R, 128);
                    load();
                    store_o();
                    if (sum8(1)) again();
                }
            } else {
                store_o();
                if (s == NSEG - 1) {
                    asm volatile("fence.proxy.async.shared::cta;" ::: "memory");
                    bar_arrive(BAR_WO, 384);
                    bar_sync(BAR_P, 128);
                    if (g == 1) share_o(sb, rank, OFF_OXL, 1);
                    break;
                }
                bar_sync(BAR_R, 128);
                if (g == 0 && s >= NVC - 1) bar_arrive(BAR_PUB, 288);
            }
            if (g == 1 && s >= NVC - 1) gather(s + 1);
            if (g == 3) asm volatile("fence.proxy.async.shared::cta;" ::: "memory");
        }
        uint32_t u, c, sb2;
        asm volatile("mov.u32 %0, %%tid.x; mov.u32 %1, %%ctaid.x; mov.u32 %2, %%dynamic_smem_size;" : "=r"(u), "=r"(c), "=r"(sb2));
        sb2 += sb - CHAIN_SMEM;
        const uint32_t g2 = __shfl_sync(0xffffffffu, (u >> 5) & 3, 0), ln = u & 31;
        asm volatile("setmaxnreg.inc.sync.aligned.u32 96;");
        const uint32_t et = lds1(sb2 + OFF_EP);
        const uint4* rp = g_tail + g2 * 8 * 2560 + c * 32 + ln;
        bf16* op = out + (size_t)((NSEG - 2) * 32 + (c & 1) * 16 + (g2 >> 1) * 8 + (ln >> 2)) * OUTW + DM + (c >> 1) * 16 + (g2 & 1) * 8 + (ln & 3) * 2;
#pragma unroll 1
        for (int t = 0; t < 2; t++) {
            if (t) bar_sync(BAR_X, 384);
            if (c >= 80) continue;
            spin(t ? TXE : TXD);
            uint4 q[8];
#pragma unroll
            for (int i = 0; i < 8; i++) q[i] = ld_pkt(rp + 2560 * i);
            for (int cnt = 4 * WAIT_LIM; cnt; cnt--) {
                uint32_t bad = 0;
#pragma unroll
                for (int i = 0; i < 8; i++) bad |= q[i].x ^ et;
                if (!any_bit0(bad, bad)) break;
                static_for<0, 8>([&](auto I) { ld_pkt_stale<I.value * 40960>(q[I.value], rp, et); });
            }
            float r[8] = {0, 0, 0, 0, 0, 0, 0, 0};
#pragma unroll
            for (int i = 0; i < 8; i++) {
                r[0] += bf_lo(q[i].x); r[1] += bf_hi(q[i].x); r[2] += bf_lo(q[i].y); r[3] += bf_hi(q[i].y);
                r[4] += bf_lo(q[i].z); r[5] += bf_hi(q[i].z); r[6] += bf_lo(q[i].w); r[7] += bf_hi(q[i].w);
            }
            const uint32_t ra = sb2 + OFF_TRED + t * 4096 + ln * 8, rb2 = ra + g2 * 1024;
#pragma unroll
            for (int j = 0; j < 4; j++) sts2(ra + j * 1024 + g2 * 256, __float_as_uint(r[2 * j]), __float_as_uint(r[2 * j + 1]));
            bar_sync(BAR_R, 128);
            const float2 x0 = lds2f(rb2), x1 = lds2f(rb2 + 256), x2 = lds2f(rb2 + 512), x3 = lds2f(rb2 + 768);
            stg1(op, movm(pack2((x0.x + x1.x) + (x2.x + x3.x), (x0.y + x1.y) + (x2.y + x3.y))));
            rp += 32 * 2560;
            op += 32 * OUTW;
        }
    }
    asm volatile("barrier.cluster.arrive.release.aligned;" ::: "memory");
    asm volatile("barrier.cluster.wait.acquire.aligned;" ::: "memory");
}

constexpr int NSIDE = 36, SST = 3, MAXJ = 44, NKS = 7;
constexpr uint32_t S_STAGE = 49152, S_STG = SST * S_STAGE, S_RST = S_STG + 65536, S_BAR = S_RST + 12288, SIDE_SMEM = S_BAR + 256;
constexpr uint32_t SB_FULL = S_BAR, SB_EMPTY = S_BAR + 64, SB_STAGED = S_BAR + 32, SB_FREE = S_BAR + 48;
constexpr uint32_t SB_FINE = 128;
enum { JV = 0, JQ = 1, JP = 2, JO = 3, JR = 4, JEND = 5 };
struct SideParams {
    bf16* out;
    CUtensorMap a[4], b[4], c[4], st[2], sto;
};
struct Job { uint32_t x, y; };
struct JobTable { Job j[NSIDE][MAXJ]; };
static_assert(OFF_OX % 1024 == 0 && OFF_QA % 1024 == 0 && OFF_MEMT % 1024 == 0, "swizzled tiles");
__constant__ const JobTable c_jobs = {{
    {{0x4020,0xa0000},{0x5220,0xa0000},{0xcc20,0xa0000},{0x641,0xa0000},{0x10341,0xa0000},{0x20640,0xa0000},{0x43,0x600000},{0x51540,0xa0000},{0x602c0,0xa0000},{0x60d40,0xa0000},{0x617c0,0xa0000},{0x40043,0x10e0400},{0x70340,0xa0000},{0x71040,0xa0000},{0x50043,0x10e0500},{0x60023,0x10e0600},{0x2360223,0x10d0605},{0x70023,0x10e0800},{0x78013,0x10e0900},{0x70024,0x1000800},{0x70224,0x1000802},{0x5,0x0},{0x40044,0x1000400},{0x50044,0x1000500},{0x60024,0x1000600},{0x68024,0x1000700}},
    {{0x40a0,0xa0000},{0x52a0,0xa0000},{0xcca0,0xa0000},{0x6c1,0xa0000},{0x103c1,0xa0000},{0x206c0,0xa0000},{0xc3,0x600000},{0x515c0,0xa0000},{0x60340,0xa0000},{0x60dc0,0xa0000},{0x50042,0xa0000},{0x400c3,0x10e0400},{0x703c0,0xa0000},{0x710c0,0xa0000},{0x500c3,0x10e0500},{0x600a3,0x10e0600},{0x680a3,0x10e0700},{0x700a3,0x10e0800},{0x78093,0x10e0900},{0x700a4,0x1000800},{0x78094,0x1000900},{0x5,0x0},{0x400c4,0x1000400},{0x500c4,0x1000500},{0x600a4,0x1000600},{0x680a4,0x1000700}},
    {{0x4120,0xa0000},{0x5320,0xa0000},{0xcd20,0xa0000},{0x741,0xa0000},{0x10441,0xa0000},{0x20740,0xa0000},{0x143,0x600000},{0x51640,0xa0000},{0x603c0,0xa0000},{0x60e40,0xa0000},{0x500c2,0xa0000},{0x40143,0x10e0400},{0x70440,0xa0000},{0x71140,0xa0000},{0x50143,0x10e0500},{0x60123,0x10e0600},{0x68123,0x10e0700},{0x70123,0x10e0800},{0x78113,0x10e0900},{0x70124,0x1000800},{0x78114,0x1000900},{0x5,0x0},{0x40144,0x1000400},{0x50144,0x1000500},{0x60124,0x1000600},{0x68124,0x1000700}},
    {{0x41a0,0xa0000},{0x53a0,0xa0000},{0xcda0,0xa0000},{0x14030,0xa0000},{0x150b0,0xa0000},{0x20341,0xa0000},{0x20dc0,0xa0000},{0x30541,0xa0000},{0x505c1,0xa0000},{0x30dc0,0xa0000},{0x602c1,0xa0000},{0x705c1,0xa0000},{0x408c0,0xa0000},{0x415c0,0xa0000},{0x505c0,0xa0000},{0x51040,0xa0000},{0x40042,0xa0000},{0x60840,0xa0000},{0x612c0,0xa0000},{0x401c3,0x10e0400},{0x600c2,0xa0000},{0x70b40,0xa0000},{0x501c3,0x10e0500},{0x700c2,0xa0000},{0x681a3,0x10e0700},{0x701a3,0x10e0800},{0x78193,0x10e0900},{0x701a4,0x1000800},{0x78194,0x1000900},{0x5,0x0},{0x401c4,0x1000400},{0x501c4,0x1000500},{0x601a4,0x1000600},{0x681a4,0x1000700}},
    {{0x4220,0xa0000},{0x5420,0xa0000},{0xce20,0xa0000},{0x140b0,0xa0000},{0x15130,0xa0000},{0x203c1,0xa0000},{0x20e40,0xa0000},{0x305c1,0xa0000},{0x50641,0xa0000},{0x30e40,0xa0000},{0x60341,0xa0000},{0x70641,0xa0000},{0x40940,0xa0000},{0x41640,0xa0000},{0x50640,0xa0000},{0x510c0,0xa0000},{0x400c2,0xa0000},{0x608c0,0xa0000},{0x61340,0xa0000},{0x40243,0x10e0400},{0x60142,0xa0000},{0x70bc0,0xa0000},{0x50243,0x10e0500},{0x70142,0xa0000},{0x68223,0x10e0700},{0x70223,0x10e0800},{0x78213,0x10e0900},{0x70224,0x1000800},{0x78214,0x1000900},{0x5,0x0},{0x40244,0x1000400},{0x50244,0x1000500},{0x60224,0x1000600},{0x68224,0x1000700}},
    {{0x42a0,0xa0000},{0x54a0,0xa0000},{0xcea0,0xa0000},{0x14130,0xa0000},{0x151b0,0xa0000},{0x20441,0xa0000},{0x20ec0,0xa0000},{0x30641,0xa0000},{0x506c1,0xa0000},{0x30ec0,0xa0000},{0x603c1,0xa0000},{0x706c1,0xa0000},{0x409c0,0xa0000},{0x416c0,0xa0000},{0x506c0,0xa0000},{0x51140,0xa0000},{0x40142,0xa0000},{0x60940,0xa0000},{0x613c0,0xa0000},{0x740043,0x10e0401},{0x601c2,0xa0000},{0x70c40,0xa0000},{0x750043,0x10e0501},{0x701c2,0xa0000},{0x768023,0x10e0701},{0x770023,0x10e0801},{0x778013,0x10e0901},{0x70024,0x1000801},{0x78014,0x1000901},{0x5,0x0},{0x40044,0x1000401},{0x50044,0x1000501},{0x60024,0x1000601},{0x68024,0x1000701}},
    {{0x4320,0xa0000},{0x5520,0xa0000},{0xcf20,0xa0000},{0x141b0,0xa0000},{0x15230,0xa0000},{0x204c1,0xa0000},{0x20f40,0xa0000},{0x306c1,0xa0000},{0x50741,0xa0000},{0x30f40,0xa0000},{0x60441,0xa0000},{0x70741,0xa0000},{0x40a40,0xa0000},{0x41740,0xa0000},{0x50740,0xa0000},{0x511c0,0xa0000},{0x401c2,0xa0000},{0x609c0,0xa0000},{0x61440,0xa0000},{0x7400c3,0x10e0401},{0x60242,0xa0000},{0x70cc0,0xa0000},{0x7500c3,0x10e0501},{0x70242,0xa0000},{0x7680a3,0x10e0701},{0x7700a3,0x10e0801},{0x778093,0x10e0901},{0x700a4,0x1000801},{0x78094,0x1000901},{0x5,0x0},{0x400c4,0x1000401},{0x500c4,0x1000501},{0x600a4,0x1000601},{0x680a4,0x1000701}},
    {{0x43a0,0xa0000},{0x55a0,0xa0000},{0xcfa0,0xa0000},{0x14230,0xa0000},{0x152b0,0xa0000},{0x20541,0xa0000},{0x20fc0,0xa0000},{0x30741,0xa0000},{0x30040,0xa0000},{0x30fc0,0xa0000},{0x604c1,0xa0000},{0x10042,0xa0000},{0x40ac0,0xa0000},{0x417c0,0xa0000},{0x507c0,0xa0000},{0x51240,0xa0000},{0x40242,0xa0000},{0x60a40,0xa0000},{0x614c0,0xa0000},{0x740143,0x10e0401},{0x70040,0xa0000},{0x70d40,0xa0000},{0x750143,0x10e0501},{0x760123,0x10e0601},{0x7600a3,0x10e0601},{0x768123,0x10e0701},{0x770123,0x10e0801},{0x778113,0x10e0901},{0x78114,0x1000901},{0x5,0x0},{0x40144,0x1000401},{0x50144,0x1000501},{0x60124,0x1000601},{0x68124,0x1000701}},
    {{0x4420,0xa0000},{0x5620,0xa0000},{0xd020,0xa0000},{0x142b0,0xa0000},{0x15330,0xa0000},{0x205c1,0xa0000},{0x21040,0xa0000},{0x40041,0xa0000},{0x300c0,0xa0000},{0x31040,0xa0000},{0x60541,0xa0000},{0x100c2,0xa0000},{0x40b40,0xa0000},{0x20043,0x600200},{0x71340,0xa0000},{0x7501c3,0x10e0501},{0x7601a3,0x10e0601},{0x7681a3,0x10e0701},{0x7701a3,0x10e0801},{0x778193,0x10e0901},{0x701a4,0x1000801},{0x78194,0x1000901},{0x5,0x0},{0x401c4,0x1000401},{0x501c4,0x1000501},{0x601a4,0x1000601},{0x681a4,0x1000701}},
    {{0x44a0,0xa0000},{0x56a0,0xa0000},{0xd0a0,0xa0000},{0x14330,0xa0000},{0x153b0,0xa0000},{0x20641,0xa0000},{0x210c0,0xa0000},{0x400c1,0xa0000},{0x30140,0xa0000},{0x310c0,0xa0000},{0x605c1,0xa0000},{0x10142,0xa0000},{0x40bc0,0xa0000},{0x200c3,0x600200},{0x713c0,0xa0000},{0x750243,0x10e0501},{0x760223,0x10e0601},{0x768223,0x10e0701},{0x770223,0x10e0801},{0x778213,0x10e0901},{0x70224,0x1000801},{0x78214,0x1000901},{0x5,0x0},{0x40244,0x1000401},{0x50244,0x1000501},{0x60224,0x1000601},{0x68224,0x1000701}},
    {{0x4520,0xa0000},{0x5720,0xa0000},{0xd120,0xa0000},{0x143b0,0xa0000},{0x15430,0xa0000},{0x206c1,0xa0000},{0x21140,0xa0000},{0x40141,0xa0000},{0x301c0,0xa0000},{0x31140,0xa0000},{0x60641,0xa0000},{0x101c2,0xa0000},{0x40c40,0xa0000},{0x20143,0x600200},{0x71440,0xa0000},{0xe50043,0x10e0502},{0xe60023,0x10e0602},{0xe68023,0x10e0702},{0xe70023,0x10e0802},{0xe78013,0x10e0902},{0x70024,0x1000802},{0x78014,0x1000902},{0x5,0x0},{0x40044,0x1000402},{0x50044,0x1000502},{0x60024,0x1000602},{0x68024,0x1000702}},
    {{0x45a0,0xa0000},{0x57a0,0xa0000},{0xd1a0,0xa0000},{0x14430,0xa0000},{0x154b0,0xa0000},{0x20741,0xa0000},{0x211c0,0xa0000},{0x401c1,0xa0000},{0x30240,0xa0000},{0x311c0,0xa0000},{0x606c1,0xa0000},{0x10242,0xa0000},{0x40cc0,0xa0000},{0x201c3,0x600200},{0x714c0,0xa0000},{0xe500c3,0x10e0502},{0xe600a3,0x10e0602},{0xe680a3,0x10e0702},{0xe700a3,0x10e0802},{0xe78093,0x10e0902},{0x700a4,0x1000802},{0x78094,0x1000902},{0x5,0x0},{0x400c4,0x1000402},{0x500c4,0x1000502},{0x600a4,0x1000602},{0x680a4,0x1000702}},
    {{0x4620,0xa0000},{0xc020,0xa0000},{0xd220,0xa0000},{0x144b0,0xa0000},{0x15530,0xa0000},{0x20040,0xa0000},{0x21240,0xa0000},{0x40241,0xa0000},{0x302c0,0xa0000},{0x31240,0xa0000},{0x60741,0xa0000},{0x40040,0xa0000},{0x40d40,0xa0000},{0x20243,0x600200},{0x71540,0xa0000},{0xe50143,0x10e0502},{0xe60123,0x10e0602},{0xe68123,0x10e0702},{0xe70123,0x10e0802},{0xe78113,0x10e0902},{0x70124,0x1000802},{0x78114,0x1000902},{0x5,0x0},{0x40144,0x1000402},{0x50144,0x1000502},{0x60124,0x1000602},{0x68124,0x1000702}},
    {{0x46a0,0xa0000},{0xc0a0,0xa0000},{0xd2a0,0xa0000},{0x14530,0xa0000},{0x155b0,0xa0000},{0x200c0,0xa0000},{0x212c0,0xa0000},{0x402c1,0xa0000},{0x30340,0xa0000},{0x312c0,0xa0000},{0x42,0xa0000},{0x400c0,0xa0000},{0x40dc0,0xa0000},{0x20042,0xa0000},{0x50840,0xa0000},{0x512c0,0xa0000},{0x60040,0xa0000},{0x60ac0,0xa0000},{0x61540,0xa0000},{0xe401c3,0x10e0402},{0x700c0,0xa0000},{0x70dc0,0xa0000},{0xe501c3,0x10e0502},{0xe601a3,0x10e0602},{0x601a3,0x10e0600},{0xe681a3,0x10e0702},{0xe701a3,0x10e0802},{0xe78193,0x10e0902},{0x78194,0x1000902},{0x5,0x0},{0x401c4,0x1000402},{0x501c4,0x1000502},{0x601a4,0x1000602},{0x681a4,0x1000702}},
    {{0x4720,0xa0000},{0xc120,0xa0000},{0xd320,0xa0000},{0x145b0,0xa0000},{0x15630,0xa0000},{0x20140,0xa0000},{0x21340,0xa0000},{0x40341,0xa0000},{0x303c0,0xa0000},{0x31340,0xa0000},{0xc2,0xa0000},{0x40140,0xa0000},{0x40e40,0xa0000},{0x200c2,0xa0000},{0x508c0,0xa0000},{0x51340,0xa0000},{0x600c0,0xa0000},{0x60b40,0xa0000},{0x615c0,0xa0000},{0xe40243,0x10e0402},{0x70140,0xa0000},{0x70e40,0xa0000},{0xe50243,0x10e0502},{0xe60223,0x10e0602},{0x60223,0x10e0600},{0xe68223,0x10e0702},{0xe70223,0x10e0802},{0xe78213,0x10e0902},{0x78214,0x1000902},{0x5,0x0},{0x40244,0x1000402},{0x50244,0x1000502},{0x60224,0x1000602},{0x68224,0x1000702}},
    {{0x47a0,0xa0000},{0xc1a0,0xa0000},{0xd3a0,0xa0000},{0x14630,0xa0000},{0x156b0,0xa0000},{0x201c0,0xa0000},{0x213c0,0xa0000},{0x403c1,0xa0000},{0x30440,0xa0000},{0x313c0,0xa0000},{0x142,0xa0000},{0x401c0,0xa0000},{0x40ec0,0xa0000},{0x20142,0xa0000},{0x50940,0xa0000},{0x513c0,0xa0000},{0x60140,0xa0000},{0x60bc0,0xa0000},{0x61640,0xa0000},{0x1540043,0x10e0403},{0x701c0,0xa0000},{0x70ec0,0xa0000},{0x1550043,0x10e0503},{0x1560023,0x10e0603},{0x23600a3,0x10d0605},{0x1568023,0x10e0703},{0x1570023,0x10e0803},{0x1578013,0x10e0903},{0x70024,0x1000803},{0x78014,0x1000903},{0x5,0x0},{0x40044,0x1000403},{0x50044,0x1000503},{0x60024,0x1000603},{0x68024,0x1000703}},
    {{0x4820,0xa0000},{0xc220,0xa0000},{0xd420,0xa0000},{0x146b0,0xa0000},{0x15730,0xa0000},{0x20240,0xa0000},{0x21440,0xa0000},{0x40441,0xa0000},{0x304c0,0xa0000},{0x31440,0xa0000},{0x1c2,0xa0000},{0x40240,0xa0000},{0x40f40,0xa0000},{0x201c2,0xa0000},{0x509c0,0xa0000},{0x51440,0xa0000},{0x601c0,0xa0000},{0x60c40,0xa0000},{0x616c0,0xa0000},{0x15400c3,0x10e0403},{0x70240,0xa0000},{0x70f40,0xa0000},{0x15500c3,0x10e0503},{0x15600a3,0x10e0603},{0x2360123,0x10d0605},{0x15680a3,0x10e0703},{0x15700a3,0x10e0803},{0x1578093,0x10e0903},{0x700a4,0x1000803},{0x78094,0x1000903},{0x5,0x0},{0x400c4,0x1000403},{0x500c4,0x1000503},{0x600a4,0x1000603},{0x680a4,0x1000703}},
    {{0x48a0,0xa0000},{0xc2a0,0xa0000},{0xd4a0,0xa0000},{0x14730,0xa0000},{0x157b0,0xa0000},{0x202c0,0xa0000},{0x214c0,0xa0000},{0x404c1,0xa0000},{0x30540,0xa0000},{0x314c0,0xa0000},{0x242,0xa0000},{0x402c0,0xa0000},{0x40fc0,0xa0000},{0x20242,0xa0000},{0x50a40,0xa0000},{0x514c0,0xa0000},{0x60240,0xa0000},{0x60cc0,0xa0000},{0x61740,0xa0000},{0x1540143,0x10e0403},{0x702c0,0xa0000},{0x70fc0,0xa0000},{0x1550143,0x10e0503},{0x1560123,0x10e0603},{0x23601a3,0x10d0605},{0x1568123,0x10e0703},{0x1570123,0x10e0803},{0x1578113,0x10e0903},{0x70124,0x1000803},{0x78114,0x1000903},{0x5,0x0},{0x40144,0x1000403},{0x50144,0x1000503},{0x60124,0x1000603},{0x68124,0x1000703}},
    {{0x4920,0xa0000},{0xc320,0xa0000},{0xd520,0xa0000},{0x147b0,0xa0000},{0x10041,0xa0000},{0x20340,0xa0000},{0x21540,0xa0000},{0x40541,0xa0000},{0x305c0,0xa0000},{0x31540,0xa0000},{0x70041,0xa0000},{0x40340,0xa0000},{0x41040,0xa0000},{0x50040,0xa0000},{0x50ac0,0xa0000},{0x516c0,0xa0000},{0x60440,0xa0000},{0x60ec0,0xa0000},{0x50142,0xa0000},{0x15401c3,0x10e0403},{0x704c0,0xa0000},{0x711c0,0xa0000},{0x15501c3,0x10e0503},{0x15601a3,0x10e0603},{0x15681a3,0x10e0703},{0x15701a3,0x10e0803},{0x1578193,0x10e0903},{0x701a4,0x1000803},{0x78194,0x1000903},{0x5,0x0},{0x401c4,0x1000403},{0x501c4,0x1000503},{0x601a4,0x1000603},{0x681a4,0x1000703}},
    {{0x49a0,0xa0000},{0xc3a0,0xa0000},{0xd5a0,0xa0000},{0x14830,0xa0000},{0x100c1,0xa0000},{0x203c0,0xa0000},{0x215c0,0xa0000},{0x405c1,0xa0000},{0x30640,0xa0000},{0x315c0,0xa0000},{0x700c1,0xa0000},{0x403c0,0xa0000},{0x410c0,0xa0000},{0x500c0,0xa0000},{0x50b40,0xa0000},{0x51740,0xa0000},{0x604c0,0xa0000},{0x60f40,0xa0000},{0x501c2,0xa0000},{0x1540243,0x10e0403},{0x70540,0xa0000},{0x71240,0xa0000},{0x1550243,0x10e0503},{0x1560223,0x10e0603},{0x1568223,0x10e0703},{0x1570223,0x10e0803},{0x1578213,0x10e0903},{0x70224,0x1000803},{0x78214,0x1000903},{0x5,0x0},{0x40244,0x1000403},{0x50244,0x1000503},{0x60224,0x1000603},{0x68224,0x1000703}},
    {{0x4a20,0xa0000},{0xc420,0xa0000},{0xd620,0xa0000},{0x148b0,0xa0000},{0x10141,0xa0000},{0x20440,0xa0000},{0x21640,0xa0000},{0x40641,0xa0000},{0x306c0,0xa0000},{0x31640,0xa0000},{0x70141,0xa0000},{0x40440,0xa0000},{0x41140,0xa0000},{0x50140,0xa0000},{0x50bc0,0xa0000},{0x517c0,0xa0000},{0x60540,0xa0000},{0x60fc0,0xa0000},{0x50242,0xa0000},{0x1c40043,0x10e0404},{0x705c0,0xa0000},{0x712c0,0xa0000},{0x1c50043,0x10e0504},{0x1c60023,0x10e0604},{0x1c68023,0x10e0704},{0x1c70023,0x10e0804},{0x1c78013,0x10e0904},{0x70024,0x1000804},{0x78014,0x1000904},{0x5,0x0},{0x40044,0x1000404},{0x50044,0x1000504},{0x60024,0x1000604},{0x68024,0x1000704}},
    {{0x4aa0,0xa0000},{0xc4a0,0xa0000},{0xd6a0,0xa0000},{0x14930,0xa0000},{0x101c1,0xa0000},{0x204c0,0xa0000},{0x216c0,0xa0000},{0x406c1,0xa0000},{0x30740,0xa0000},{0x316c0,0xa0000},{0x701c1,0xa0000},{0x404c0,0xa0000},{0x411c0,0xa0000},{0x501c0,0xa0000},{0x50c40,0xa0000},{0x30042,0xa0000},{0x605c0,0xa0000},{0x61040,0xa0000},{0x1c400c3,0x10e0404},{0x29c00c3,0x10d0406},{0x706c0,0xa0000},{0x71640,0xa0000},{0x1c500c3,0x10e0504},{0x1c600a3,0x10e0604},{0x1c680a3,0x10e0704},{0x1c700a3,0x10e0804},{0x1c78093,0x10e0904},{0x700a4,0x1000804},{0x78094,0x1000904},{0x5,0x0},{0x400c4,0x1000404},{0x500c4,0x1000504},{0x600a4,0x1000604},{0x680a4,0x1000704}},
    {{0x4b20,0xa0000},{0xc520,0xa0000},{0xd720,0xa0000},{0x149b0,0xa0000},{0x10241,0xa0000},{0x20540,0xa0000},{0x21740,0xa0000},{0x40741,0xa0000},{0x307c0,0xa0000},{0x31740,0xa0000},{0x70241,0xa0000},{0x40540,0xa0000},{0x41240,0xa0000},{0x50240,0xa0000},{0x50cc0,0xa0000},{0x300c2,0xa0000},{0x60640,0xa0000},{0x610c0,0xa0000},{0x1c40143,0x10e0404},{0x29c0143,0x10d0406},{0x70740,0xa0000},{0x716c0,0xa0000},{0x1c50143,0x10e0504},{0x1c60123,0x10e0604},{0x1c68123,0x10e0704},{0x1c70123,0x10e0804},{0x1c78113,0x10e0904},{0x70124,0x1000804},{0x78114,0x1000904},{0x5,0x0},{0x40144,0x1000404},{0x50144,0x1000504},{0x60124,0x1000604},{0x68124,0x1000704}},
    {{0x4ba0,0xa0000},{0xc5a0,0xa0000},{0xd7a0,0xa0000},{0x14a30,0xa0000},{0x102c1,0xa0000},{0x205c0,0xa0000},{0x217c0,0xa0000},{0x50041,0xa0000},{0x30840,0xa0000},{0x317c0,0xa0000},{0x702c1,0xa0000},{0x405c0,0xa0000},{0x412c0,0xa0000},{0x502c0,0xa0000},{0x50d40,0xa0000},{0x30142,0xa0000},{0x606c0,0xa0000},{0x61140,0xa0000},{0x1c401c3,0x10e0404},{0x29c01c3,0x10d0406},{0x707c0,0xa0000},{0x71740,0xa0000},{0x1c501c3,0x10e0504},{0x1c601a3,0x10e0604},{0x1c681a3,0x10e0704},{0x1c701a3,0x10e0804},{0x1c78193,0x10e0904},{0x701a4,0x1000804},{0x78194,0x1000904},{0x5,0x0},{0x401c4,0x1000404},{0x501c4,0x1000504},{0x601a4,0x1000604},{0x681a4,0x1000704}},
    {{0x4c20,0xa0000},{0xc620,0xa0000},{0x41,0xa0000},{0x14ab0,0xa0000},{0x104c1,0xa0000},{0x207c0,0xa0000},{0x1c3,0x600000},{0x301c2,0xa0000},{0x60740,0xa0000},{0x611c0,0xa0000},{0x1c40243,0x10e0404},{0x60042,0xa0000},{0x70640,0xa0000},{0x715c0,0xa0000},{0x1c50243,0x10e0504},{0x1c60223,0x10e0604},{0x1c68223,0x10e0704},{0x1c70223,0x10e0804},{0x1c78213,0x10e0904},{0x70224,0x1000804},{0x78214,0x1000904},{0x5,0x0},{0x40244,0x1000404},{0x50244,0x1000504},{0x60224,0x1000604},{0x68224,0x1000704}},
    {{0x4ca0,0xa0000},{0xc6a0,0xa0000},{0xc1,0xa0000},{0x14b30,0xa0000},{0x10541,0xa0000},{0x20840,0xa0000},{0x243,0x600000},{0x30242,0xa0000},{0x607c0,0xa0000},{0x61240,0xa0000},{0x2340043,0x10d0405},{0x29c0243,0x10d0406},{0x70840,0xa0000},{0x717c0,0xa0000},{0x2350043,0x10d0505},{0x2360023,0x10d0605},{0x2368023,0x10d0705},{0x2370023,0x10d0805},{0x2378013,0x10d0905},{0x70024,0x1000805},{0x78014,0x1000905},{0x5,0x0},{0x40044,0x1000405},{0x50044,0x1000505},{0x60024,0x1000605},{0x68024,0x1000705}},
    {{0x4d20,0xa0000},{0xc720,0xa0000},{0x141,0xa0000},{0x14bb0,0xa0000},{0x105c1,0xa0000},{0x208c0,0xa0000},{0x30041,0xa0000},{0x500c1,0xa0000},{0x308c0,0xa0000},{0x10043,0x600100},{0x23400c3,0x10d0405},{0xe40043,0x10e0402},{0x708c0,0xa0000},{0x23500c3,0x10d0505},{0x29d00c3,0x10d0506},{0x23680a3,0x10d0705},{0x23700a3,0x10d0805},{0x2378093,0x10d0905},{0x700a4,0x1000805},{0x78094,0x1000905},{0x5,0x0},{0x400c4,0x1000405},{0x500c4,0x1000505},{0x600a4,0x1000605},{0x680a4,0x1000705}},
    {{0x4da0,0xa0000},{0xc7a0,0xa0000},{0x1c1,0xa0000},{0x14c30,0xa0000},{0x10641,0xa0000},{0x20940,0xa0000},{0x300c1,0xa0000},{0x50141,0xa0000},{0x30940,0xa0000},{0x100c3,0x600100},{0x2340143,0x10d0405},{0xe400c3,0x10e0402},{0x70940,0xa0000},{0x2350143,0x10d0505},{0x29d0143,0x10d0506},{0x2368123,0x10d0705},{0x2370123,0x10d0805},{0x2378113,0x10d0905},{0x70124,0x1000805},{0x78114,0x1000905},{0x5,0x0},{0x40144,0x1000405},{0x50144,0x1000505},{0x60124,0x1000605},{0x68124,0x1000705}},
    {{0x4e20,0xa0000},{0xc820,0xa0000},{0x241,0xa0000},{0x14cb0,0xa0000},{0x106c1,0xa0000},{0x209c0,0xa0000},{0x30141,0xa0000},{0x501c1,0xa0000},{0x309c0,0xa0000},{0x10143,0x600100},{0x23401c3,0x10d0405},{0xe40143,0x10e0402},{0x709c0,0xa0000},{0x23501c3,0x10d0505},{0x29d01c3,0x10d0506},{0x23681a3,0x10d0705},{0x23701a3,0x10d0805},{0x2378193,0x10d0905},{0x701a4,0x1000805},{0x78194,0x1000905},{0x5,0x0},{0x401c4,0x1000405},{0x501c4,0x1000505},{0x601a4,0x1000605},{0x681a4,0x1000705}},
    {{0x4ea0,0xa0000},{0xc8a0,0xa0000},{0x2c1,0xa0000},{0x14d30,0xa0000},{0x10741,0xa0000},{0x20a40,0xa0000},{0x301c1,0xa0000},{0x50241,0xa0000},{0x30a40,0xa0000},{0x101c3,0x600100},{0x2340243,0x10d0405},{0x7401c3,0x10e0401},{0x70a40,0xa0000},{0x2350243,0x10d0505},{0x29d0243,0x10d0506},{0x2368223,0x10d0705},{0x2370223,0x10d0805},{0x2378213,0x10d0905},{0x70224,0x1000805},{0x78214,0x1000905},{0x5,0x0},{0x40244,0x1000405},{0x50244,0x1000505},{0x60224,0x1000605},{0x68224,0x1000705}},
    {{0x4f20,0xa0000},{0xc920,0xa0000},{0x341,0xa0000},{0x14db0,0xa0000},{0x20041,0xa0000},{0x20ac0,0xa0000},{0x30241,0xa0000},{0x502c1,0xa0000},{0x30ac0,0xa0000},{0x10243,0x600100},{0x29c0043,0x10d0406},{0x740243,0x10e0401},{0x70ac0,0xa0000},{0x29d0043,0x10d0506},{0x70042,0xa0000},{0x29e0023,0x10d0606},{0x29e8023,0x10d0706},{0x29f0023,0x10d0806},{0x29f8013,0x10d0906},{0x70024,0x1000806},{0x78014,0x1000906},{0x5,0x0},{0x40044,0x1000406},{0x50044,0x1000506},{0x60024,0x1000606},{0x68024,0x1000706}},
    {{0x4fa0,0xa0000},{0xc9a0,0xa0000},{0x3c1,0xa0000},{0x14e30,0xa0000},{0x200c1,0xa0000},{0x20b40,0xa0000},{0x302c1,0xa0000},{0x50341,0xa0000},{0x30b40,0xa0000},{0x60041,0xa0000},{0x70341,0xa0000},{0x40640,0xa0000},{0x41340,0xa0000},{0x50340,0xa0000},{0x50dc0,0xa0000},{0x30043,0x600300},{0x29e00a3,0x10d0606},{0x29e80a3,0x10d0706},{0x29f00a3,0x10d0806},{0x29f8093,0x10d0906},{0x700a4,0x1000806},{0x78094,0x1000906},{0x5,0x0},{0x400c4,0x1000406},{0x500c4,0x1000506},{0x600a4,0x1000606},{0x680a4,0x1000706}},
    {{0x5020,0xa0000},{0xca20,0xa0000},{0x441,0xa0000},{0x14eb0,0xa0000},{0x20141,0xa0000},{0x20bc0,0xa0000},{0x30341,0xa0000},{0x503c1,0xa0000},{0x30bc0,0xa0000},{0x600c1,0xa0000},{0x703c1,0xa0000},{0x406c0,0xa0000},{0x413c0,0xa0000},{0x503c0,0xa0000},{0x50e40,0xa0000},{0x300c3,0x600300},{0x29e0123,0x10d0606},{0x29e8123,0x10d0706},{0x29f0123,0x10d0806},{0x29f8113,0x10d0906},{0x70124,0x1000806},{0x78114,0x1000906},{0x5,0x0},{0x40144,0x1000406},{0x50144,0x1000506},{0x60124,0x1000606},{0x68124,0x1000706}},
    {{0x50a0,0xa0000},{0xcaa0,0xa0000},{0x4c1,0xa0000},{0x14f30,0xa0000},{0x201c1,0xa0000},{0x20c40,0xa0000},{0x303c1,0xa0000},{0x50441,0xa0000},{0x30c40,0xa0000},{0x60141,0xa0000},{0x70441,0xa0000},{0x40740,0xa0000},{0x41440,0xa0000},{0x50440,0xa0000},{0x50ec0,0xa0000},{0x30143,0x600300},{0x29e01a3,0x10d0606},{0x29e81a3,0x10d0706},{0x29f01a3,0x10d0806},{0x29f8193,0x10d0906},{0x701a4,0x1000806},{0x78194,0x1000906},{0x5,0x0},{0x401c4,0x1000406},{0x501c4,0x1000506},{0x601a4,0x1000606},{0x681a4,0x1000706}},
    {{0x5120,0xa0000},{0xcb20,0xa0000},{0x541,0xa0000},{0x14fb0,0xa0000},{0x20241,0xa0000},{0x20cc0,0xa0000},{0x30441,0xa0000},{0x504c1,0xa0000},{0x30cc0,0xa0000},{0x601c1,0xa0000},{0x704c1,0xa0000},{0x407c0,0xa0000},{0x414c0,0xa0000},{0x504c0,0xa0000},{0x50f40,0xa0000},{0x301c3,0x600300},{0x29e0223,0x10d0606},{0x29e8223,0x10d0706},{0x29f0223,0x10d0806},{0x29f8213,0x10d0906},{0x70224,0x1000806},{0x78214,0x1000906},{0x5,0x0},{0x40244,0x1000406},{0x50244,0x1000506},{0x60224,0x1000606},{0x68224,0x1000706}},
    {{0x51a0,0xa0000},{0xcba0,0xa0000},{0x5c1,0xa0000},{0x15030,0xa0000},{0x202c1,0xa0000},{0x20d40,0xa0000},{0x304c1,0xa0000},{0x50541,0xa0000},{0x30d40,0xa0000},{0x60241,0xa0000},{0x70541,0xa0000},{0x40840,0xa0000},{0x41540,0xa0000},{0x50540,0xa0000},{0x50fc0,0xa0000},{0x30243,0x600300},{0x760023,0x10e0601},{0x68023,0x10e0700},{0x70124,0x1000801},{0x701a4,0x1000802},{0x78014,0x1000900},{0x5,0x0}},
}};
#define D8(i) "+f"(d[i]), "+f"(d[i + 1]), "+f"(d[i + 2]), "+f"(d[i + 3]), "+f"(d[i + 4]), "+f"(d[i + 5]), "+f"(d[i + 6]), "+f"(d[i + 7])
template <int N> __device__ __forceinline__ void wgmma_side(float* d, uint32_t alo, uint32_t blo, int sc);
template <> __device__ __forceinline__ void wgmma_side<64>(float* d, uint32_t alo, uint32_t blo, int sc) {
    asm volatile("{.reg .pred p; .reg .b64 ad, bd; setp.ne.b32 p, %34, 0; mov.b64 ad, {%32, 0x40000040}; mov.b64 bd, {%33, 0x40000040};\n"
                 "wgmma.mma_async.sync.aligned.m64n64k16.f32.bf16.bf16 "
                 "{%0,%1,%2,%3,%4,%5,%6,%7,%8,%9,%10,%11,%12,%13,%14,%15,%16,%17,%18,%19,%20,%21,%22,%23,%24,%25,%26,%27,%28,%29,%30,%31},"
                 " ad, bd, p, 1, 1, 1, 0;}"
                 : D8(0), D8(8), D8(16), D8(24)
                 : "r"(alo), "r"(blo), "r"(sc));
}
template <> __device__ __forceinline__ void wgmma_side<128>(float* d, uint32_t alo, uint32_t blo, int sc) {
    asm volatile("{.reg .pred p; .reg .b64 ad, bd; setp.ne.b32 p, %66, 0; mov.b64 ad, {%64, 0x40000040}; mov.b64 bd, {%65, 0x40000040};\n"
                 "wgmma.mma_async.sync.aligned.m64n128k16.f32.bf16.bf16 "
                 "{%0,%1,%2,%3,%4,%5,%6,%7,%8,%9,%10,%11,%12,%13,%14,%15,%16,%17,%18,%19,%20,%21,%22,%23,%24,%25,%26,%27,%28,%29,%30,%31,"
                 "%32,%33,%34,%35,%36,%37,%38,%39,%40,%41,%42,%43,%44,%45,%46,%47,%48,%49,%50,%51,%52,%53,%54,%55,%56,%57,%58,%59,%60,%61,%62,%63},"
                 " ad, bd, p, 1, 1, 1, 0;}"
                 : D8(0), D8(8), D8(16), D8(24), D8(32), D8(40), D8(48), D8(56)
                 : "r"(alo), "r"(blo), "r"(sc));
}
template <> __device__ __forceinline__ void wgmma_side<192>(float* d, uint32_t alo, uint32_t blo, int sc) {
    asm volatile("{.reg .pred p; .reg .b64 ad, bd; setp.ne.b32 p, %98, 0; mov.b64 ad, {%96, 0x40000040}; mov.b64 bd, {%97, 0x40000040};\n"
                 "wgmma.mma_async.sync.aligned.m64n192k16.f32.bf16.bf16 "
                 "{%0,%1,%2,%3,%4,%5,%6,%7,%8,%9,%10,%11,%12,%13,%14,%15,%16,%17,%18,%19,%20,%21,%22,%23,%24,%25,%26,%27,%28,%29,%30,%31,"
                 "%32,%33,%34,%35,%36,%37,%38,%39,%40,%41,%42,%43,%44,%45,%46,%47,%48,%49,%50,%51,%52,%53,%54,%55,%56,%57,%58,%59,%60,%61,%62,%63,"
                 "%64,%65,%66,%67,%68,%69,%70,%71,%72,%73,%74,%75,%76,%77,%78,%79,%80,%81,%82,%83,%84,%85,%86,%87,%88,%89,%90,%91,%92,%93,%94,%95},"
                 " ad, bd, p, 1, 1, 1, 0;}"
                 : D8(0), D8(8), D8(16), D8(24), D8(32), D8(40), D8(48), D8(56), D8(64), D8(72), D8(80), D8(88)
                 : "r"(alo), "r"(blo), "r"(sc));
}
template <> __device__ __forceinline__ void wgmma_side<256>(float* d, uint32_t alo, uint32_t blo, int sc) {
    asm volatile("{.reg .pred p; .reg .b64 ad, bd; setp.ne.b32 p, %130, 0; mov.b64 ad, {%128, 0x40000040}; mov.b64 bd, {%129, 0x40000040};\n"
                 "wgmma.mma_async.sync.aligned.m64n256k16.f32.bf16.bf16 "
                 "{%0,%1,%2,%3,%4,%5,%6,%7,%8,%9,%10,%11,%12,%13,%14,%15,%16,%17,%18,%19,%20,%21,%22,%23,%24,%25,%26,%27,%28,%29,%30,%31,"
                 "%32,%33,%34,%35,%36,%37,%38,%39,%40,%41,%42,%43,%44,%45,%46,%47,%48,%49,%50,%51,%52,%53,%54,%55,%56,%57,%58,%59,%60,%61,%62,%63,"
                 "%64,%65,%66,%67,%68,%69,%70,%71,%72,%73,%74,%75,%76,%77,%78,%79,%80,%81,%82,%83,%84,%85,%86,%87,%88,%89,%90,%91,%92,%93,%94,%95,"
                 "%96,%97,%98,%99,%100,%101,%102,%103,%104,%105,%106,%107,%108,%109,%110,%111,%112,%113,%114,%115,%116,%117,%118,%119,%120,%121,%122,%123,%124,%125,%126,%127},"
                 " ad, bd, p, 1, 1, 1, 0;}"
                 : D8(0), D8(8), D8(16), D8(24), D8(32), D8(40), D8(48), D8(56), D8(64), D8(72), D8(80), D8(88), D8(96), D8(104), D8(112), D8(120)
                 : "r"(alo), "r"(blo), "r"(sc));
}
#define W8(i) "=f"(d[i]), "=f"(d[i + 1]), "=f"(d[i + 2]), "=f"(d[i + 3]), "=f"(d[i + 4]), "=f"(d[i + 5]), "=f"(d[i + 6]), "=f"(d[i + 7])
__device__ __forceinline__ void wgmma_first(float* d, uint32_t alo, uint32_t blo) {
    asm volatile("{.reg .pred p; .reg .b64 ad, bd; setp.ne.b32 p, %130, 0; mov.b64 ad, {%128, 0x40000040}; mov.b64 bd, {%129, 0x40000040};\n"
                 "wgmma.mma_async.sync.aligned.m64n256k16.f32.bf16.bf16 "
                 "{%0,%1,%2,%3,%4,%5,%6,%7,%8,%9,%10,%11,%12,%13,%14,%15,%16,%17,%18,%19,%20,%21,%22,%23,%24,%25,%26,%27,%28,%29,%30,%31,"
                 "%32,%33,%34,%35,%36,%37,%38,%39,%40,%41,%42,%43,%44,%45,%46,%47,%48,%49,%50,%51,%52,%53,%54,%55,%56,%57,%58,%59,%60,%61,%62,%63,"
                 "%64,%65,%66,%67,%68,%69,%70,%71,%72,%73,%74,%75,%76,%77,%78,%79,%80,%81,%82,%83,%84,%85,%86,%87,%88,%89,%90,%91,%92,%93,%94,%95,"
                 "%96,%97,%98,%99,%100,%101,%102,%103,%104,%105,%106,%107,%108,%109,%110,%111,%112,%113,%114,%115,%116,%117,%118,%119,%120,%121,%122,%123,%124,%125,%126,%127},"
                 " ad, bd, p, 1, 1, 1, 0;}"
                 : W8(0), W8(8), W8(16), W8(24), W8(32), W8(40), W8(48), W8(56), W8(64), W8(72), W8(80), W8(88), W8(96), W8(104), W8(112), W8(120)
                 : "r"(alo), "r"(blo), "n"(0));
}
#undef W8
#undef D8

__device__ __forceinline__ void bulk_st(void* dst, uint32_t src, uint32_t bytes) {
    asm volatile("cp.async.bulk.global.shared::cta.bulk_group [%0], [%1], %2;" :: "l"(dst), "r"(src), "r"(bytes) : "memory");
}
__device__ __forceinline__ void red_release(uint32_t* p, uint32_t v) { asm volatile("red.release.gpu.global.add.u32 [%0], %1;" :: "l"(p), "r"(v) : "memory"); }
__device__ __forceinline__ void wait_ge(const uint32_t* p, uint32_t v) { for (int c = 0; c < SPIN_LIM && (int)(ld_acquire(p) - v) < 0; c++) { } }
__device__ __forceinline__ uint4* part_ptr(Job job, int wg) {
    return g_op + (size_t)((job.x >> 13) & 63) * (10 * NKS * 256) + (((job.x >> 7) & 63) * 2 + wg) * NKS * ((job.x >> 3) & 15) * 256;
}

template <int T>
__device__ __forceinline__ void side_job(Job job, uint32_t& it, uint32_t& n, uint32_t sb, uint32_t sa, int wg, int t)
{
    float acc[T / 2];
    const int nkb = job.y >> 16 & 255;
    constexpr uint32_t NS = T == 64 ? 2 * SST : SST, SZ = SST * S_STAGE / NS, BO = T == 64 ? SB_FINE : 0;
    constexpr bool peel = T == 256;
    uint32_t prev = 0;
    auto block = [&](int kb, auto FIRST) {
        const uint32_t st = it % NS;
        const uint32_t alo = ((sb + st * SZ + wg * 8192) >> 4) | (64u << 16), blo = ((sb + st * SZ + 16384) >> 4) | (1u << 16);
        mbar_wait_long(sb + SB_FULL + BO + 8 * st, (it / NS) & 1);
        wg_fence();
        if constexpr (FIRST.value) wgmma_first(acc, alo, blo);
#pragma unroll
        for (int k4 = FIRST.value; k4 < 4; k4++) wgmma_side<T>(acc, alo + k4 * 128, blo + k4 * 2, peel ? 1 : kb | k4);
        wg_commit();
        if (peel ? !FIRST.value : kb) { wg_wait<1>(); arrive_e(prev); }
        prev = sb + SB_EMPTY + BO + 8 * st;
        it++;
    };
    if constexpr (peel) block(0, IC<1>());
    else {
#pragma unroll
        for (int i = 0; i < T / 2; i++) acc[i] = 0.f;
    }
    for (int kb = peel; kb < nkb; kb++) block(kb, IC<0>());
    if (n) mbar_wait_long(sb + SB_FREE, (n - 1) & 1);
    n++;
    wg_wait<0>();
    arrive_e(prev);
    const bool raw = (job.x & 7) == JV || job.y >> 24;
#pragma unroll
    for (int u = 0; u < T / 16; u++) {
        const uint4 w = make_uint4(pack2(acc[8 * u], acc[8 * u + 1]), pack2(acc[8 * u + 2], acc[8 * u + 3]),
                                   pack2(acc[8 * u + 4], acc[8 * u + 5]), pack2(acc[8 * u + 6], acc[8 * u + 7]));
        if (raw || T != 256) sts4(sb + S_STG + wg * 32768 + t * 16 + u * 2048, make_uint4(w.x, w.z, w.y, w.w));
        else stsm4t(sb + S_STG + wg * 32768 + sa + u * 2048, w.x, w.y, w.z, w.w);
    }
    __syncwarp();
    arrive_e(sb + SB_STAGED + 8 * wg);
}

__device__ __forceinline__ void ld20(const bf16* p, uint32_t* w) {
#pragma unroll
    for (int i = 0; i < 5; i++) asm volatile("ld.global.v2.b32 {%0,%1}, [%2];" : "=r"(w[2 * i]), "=r"(w[2 * i + 1]) : "l"(p + 4 * i) : "memory");
}

__global__ void __launch_bounds__(384, 1) side_kernel(const __grid_constant__ SideParams P)
{
    extern __shared__ __align__(1024) uint8_t smem[];
    const uint32_t sb = smem_u32(smem);
    const int tid = threadIdx.x, lane = tid & 31;
    const int warp = __shfl_sync(0xffffffffu, tid >> 5, 0);
    if (tid == 0) {
        for (int i = 0; i < SST; i++) { mbar_init(sb + SB_FULL + 8 * i, 1); mbar_init(sb + SB_EMPTY + 8 * i, 8); }
        for (int i = 0; i < 2 * SST; i++) { mbar_init(sb + SB_FULL + SB_FINE + 8 * i, 1); mbar_init(sb + SB_EMPTY + SB_FINE + 8 * i, 8); }
        mbar_init(sb + SB_STAGED, 4); mbar_init(sb + SB_STAGED + 8, 4); mbar_init(sb + SB_FREE, 1);
        asm volatile("fence.mbarrier_init.release.cluster;" ::: "memory");
    }
    __syncthreads();
    const Job* jobs = c_jobs.j[blockIdx.x];
    if (warp < 8) {
        asm volatile("setmaxnreg.inc.sync.aligned.u32 192;");
        const uint32_t ep = ld_epoch();
        uint32_t it = 0, it2 = 0, n = 0;
        const int wg = warp >> 2, t = tid & 127;
        const uint32_t sa = ((lane & 7) + ((lane >> 4) << 3)) * 128 + (((2 * (t >> 5) + ((lane >> 3) & 1)) ^ (lane & 7)) << 4);
        for (int j = 0; ; j++) {
            const Job job = jobs[j];
            const int type = job.x & 7, nb = (job.x >> 3) & 15;
            if (type == JEND) break;
            if (type == JR) {
                const int ks = job.y & 15, ct = (job.x >> 7) & 63;
                if (t == 0) {
                    asm volatile("cp.async.bulk.wait_group.read 0;" ::: "memory");
                    wait_ge(g_cnt + CNT_O + (job.y >> 8 & 255) * 5 + ct, ep * NKS);
                }
                bar_sync(1 + wg, 128);
                const uint4* part = part_ptr(job, wg) + ks * 128 + t;
                const uint32_t rs = sb + S_RST + wg * 6144;
                uint4 q[3][NKS];
#pragma unroll
                for (int i = 0; i < 3; i++) {
#pragma unroll
                    for (int k = 0; k < NKS; k++) q[i][k] = make_uint4(0, 0, 0, 0);
                    if (ks + i * NKS < 2 * nb) {
#pragma unroll
                        for (int k = 0; k < NKS; k++) q[i][k] = ld_pkt(part + k * nb * 256 + i * NKS * 128);
                    }
                }
#pragma unroll
                for (int i = 0; i < 3; i++)
                    if (ks + i * NKS < 2 * nb) {
                        float r[8] = {0, 0, 0, 0, 0, 0, 0, 0};
#pragma unroll
                        for (int k = 0; k < NKS; k++) {
                            r[0] += bf_lo(q[i][k].x); r[1] += bf_hi(q[i][k].x); r[2] += bf_lo(q[i][k].y); r[3] += bf_hi(q[i][k].y);
                            r[4] += bf_lo(q[i][k].z); r[5] += bf_hi(q[i][k].z); r[6] += bf_lo(q[i][k].w); r[7] += bf_hi(q[i][k].w);
                        }
                        stsm4t(rs + sa + i * 2048, pack2(r[0], r[1]), pack2(r[4], r[5]), pack2(r[2], r[3]), pack2(r[6], r[7]));
                    }
                asm volatile("fence.proxy.async.shared::cta;" ::: "memory");
                bar_sync(1 + wg, 128);
                if (t == 0) {
                    for (int i = 0; i < 3; i++)
                        if (ks + i * NKS < 2 * nb) tma_st(&P.sto, rs + i * 2048, DM + ct * 128 + wg * 64, ((job.x >> 13) & 63) * 32 + (ks + i * NKS) * 16);
                    asm volatile("cp.async.bulk.commit_group;" ::: "memory");
                }
                __syncwarp();
                continue;
            }
            switch (nb) {
                case 8: side_job<256>(job, it, n, sb, sa, wg, t); break;
                case 6: side_job<192>(job, it, n, sb, sa, wg, t); break;
                case 4: side_job<128>(job, it, n, sb, sa, wg, t); break;
                default: side_job<64>(job, it2, n, sb, sa, wg, t); break;
            }
        }
        if (t == 0) asm volatile("cp.async.bulk.wait_group 0;" ::: "memory");
    } else {
        asm volatile("setmaxnreg.dec.sync.aligned.u32 120;");
        if (warp == 8) {
            uint32_t ep = 0, ns = SST, sz = S_STAGE, bo = sb, sa = 0, pa = 1, sl = 0;
            for (int j = 0; ; j++) {
                const Job job = jobs[j];
                const int type = job.x & 7;
                if (type == JEND) break;
                if (type == JR) continue;
                const int nb = (job.x >> 3) & 15, c0 = ((job.x >> 7) & 63) * 2, seg0 = (job.x >> 13) & 63, kb0 = (job.x >> 19) & 127,
                          nkb = job.y >> 16 & 255;
                const CUtensorMap *ta = &P.a[type], *tb = nb == 8 ? &P.b[type] : &P.c[(type == JV ? 3 : 4) - nb / 2];
                auto ready = [&]() {
                    bool ok = true;
                    if (type == JP) ok = (int)(ld_acquire(g_cnt + CNT_ATT + (seg0 >> 3)) - ep * 256) >= 0;
                    else
                        for (int i = 0; i < nkb; i += 32) ok &= (int)(ld_acquire(g_prog + kb0 + min(i + lane, nkb - 1)) - (ep * 128 + seg0 + nb)) >= 0;
                    return __all_sync(0xffffffffu, ok);
                };
                if (nb == 2 && ns == SST) {
                    for (uint32_t i = 0; i < SST; i++) mbar_wait_long(sb + SB_EMPTY + 8 * i, pa ^ (i < sa));
                    ns = 2 * SST; sz = S_STAGE / 2; bo = sb + SB_FINE; sa = 0; pa = 1; sl = 0;
                }
                auto loadA = [&](int kb) {
                    const uint32_t full = bo + SB_FULL + 8 * sa;
                    mbar_wait_long(bo + SB_EMPTY + 8 * sa, pa);
                    expect_e(full, 16384 + nb * 4096);
                    tma3d_e(sb + sa * sz, ta, (kb0 + kb) * 64, c0, full);
                    if (++sa == ns) { sa = 0; pa ^= 1; }
                };
                auto loadB = [&](int kb) {
                    tma2d_e(sb + sl * sz + 16384, tb, (kb0 + kb) * 64, seg0 * 32, bo + SB_FULL + 8 * sl);
                    if (++sl == ns) sl = 0;
                };
                int pre = 0;
                if (type >= JP) {
                    if (!ready()) {
                        pre = ns;
#pragma unroll 1
                        for (int kb = 0; kb < pre; kb++) loadA(kb);
                        for (int c = 0; c < SPIN_LIM && !ready(); c++) { }
                    }
                    asm volatile("fence.proxy.async.global;" ::: "memory");
                }
#pragma unroll 1
                for (int kb = 0; kb < nkb; kb++) { if (kb >= pre) loadA(kb); loadB(kb); }
                if (j == 0) ep = ld_epoch();
            }
            if (blockIdx.x == 0 && lane == 0) g_epoch = ep;
        } else if (warp == 9) {
            if (lane == 0) {
                const uint32_t ep = ld_epoch();
                uint32_t n = 0;
                for (int j = 0; ; j++) {
                    const Job job = jobs[j];
                    const int type = job.x & 7;
                    if (type == JEND) break;
                    if (type == JR) continue;
                    const int nb = (job.x >> 3) & 15, ct = (job.x >> 7) & 63, seg0 = (job.x >> 13) & 63;
                    for (int wg = 0; wg < 2; wg++) {
                        const uint32_t src = sb + S_STG + wg * 32768;
                        mbar_wait_long(sb + SB_STAGED + 8 * wg, n & 1);
                        asm volatile("fence.proxy.async.shared::cta;" ::: "memory");
                        if (type == JV) bulk_st(g_vx + ((ct * 2 + wg) * 64 + seg0) * 256, src, nb * 4096);
                        else if (job.y >> 24) bulk_st(part_ptr(job, wg) + (job.y & 15) * nb * 256, src, nb * 4096);
                        else tma_st(&P.st[type != JQ], src, (type == JO ? DM : 0) + ct * 128 + wg * 64, seg0 * 32);
                    }
                    asm volatile("cp.async.bulk.commit_group;" ::: "memory");
                    asm volatile("cp.async.bulk.wait_group.read 0;" ::: "memory");
                    mbar_arrive(sb + SB_FREE);
                    asm volatile("cp.async.bulk.wait_group 0;" ::: "memory");
                    if (type == JV) { st_release(g_flagv + ct * 128 + seg0, ep); g_flagv[ct * 128 + 64 + seg0] = ep; }
                    if (type == JQ) red_release(g_cnt + CNT_Q + (seg0 >> 3), 1);
                    if (job.y >> 24) red_release(g_cnt + CNT_O + (job.y >> 8 & 255) * 5 + ct, 1);
                    n++;
                }
            }
        } else {
            const uint32_t ep = ld_epoch();
            const float scl = 0.22360679774997896f * 1.4426950408889634f;
            for (int p = blockIdx.x * 2 + warp - 10; p < SEQ / 2; p += 2 * NSIDE) {
                const int t0 = 4 * (p >> 1) + (p & 1);
                wait_ge(g_cnt + CNT_Q + (max(t0 - 14, 0) >> 8), ep * 15);
                wait_ge(g_cnt + CNT_Q + (t0 >> 8), ep * 15);
                const bf16* base = g_qkvA + lane * 20;
                uint32_t w[18][10];
                auto row = [&](int j) { if (j < 18) ld20(base + (size_t)max(t0 + 2 - 2 * (j % 9), 0) * 1920 + (j < 9 ? 640 : 1280), w[j]); };
                float l0[8], l1[8];
                {
                    uint32_t u0[10], u1[10];
                    float q0[20], q1[20];
                    ld20(base + (size_t)t0 * 1920, u0); ld20(base + (size_t)(t0 + 2) * 1920, u1);
                    row(0); row(1);
#pragma unroll
                    for (int i = 0; i < 10; i++) { q0[2 * i] = bf_lo(u0[i]); q0[2 * i + 1] = bf_hi(u0[i]); q1[2 * i] = bf_lo(u1[i]); q1[2 * i + 1] = bf_hi(u1[i]); }
#pragma unroll
                    for (int j = 0; j < 9; j++) {
                        row(j + 2);
                        blk(warp);
                        float a0 = 0.f, a1 = 0.f;
#pragma unroll
                        for (int i = 0; i < 10; i++) {
                            const float lo = bf_lo(w[j][i]), hi = bf_hi(w[j][i]);
                            if (j > 0) a0 = fmaf(q0[2 * i + 1], hi, fmaf(q0[2 * i], lo, a0));
                            if (j < 8) a1 = fmaf(q1[2 * i + 1], hi, fmaf(q1[2 * i], lo, a1));
                        }
                        const bool in = t0 + 2 - 2 * j >= 0;
                        if (j > 0) l0[j - 1] = in ? a0 * scl : -3.0e38f;
                        if (j < 8) l1[j] = in ? a1 * scl : -3.0e38f;
                    }
                }
                float m0 = l0[0], m1 = l1[0], s0 = 0.f, s1 = 0.f;
#pragma unroll
                for (int j = 1; j < 8; j++) { m0 = fmaxf(m0, l0[j]); m1 = fmaxf(m1, l1[j]); }
#pragma unroll
                for (int j = 0; j < 8; j++) { l0[j] = ex2(l0[j] - m0); s0 += l0[j]; l1[j] = ex2(l1[j] - m1); s1 += l1[j]; }
                float o0[20], o1[20];
#pragma unroll
                for (int i = 0; i < 20; i++) o0[i] = o1[i] = 0.f;
#pragma unroll
                for (int j = 0; j < 9; j++) {
                    row(j + 11);
                    blk(warp);
#pragma unroll
                    for (int i = 0; i < 10; i++) {
                        const float lo = bf_lo(w[9 + j][i]), hi = bf_hi(w[9 + j][i]);
                        if (j > 0) { o0[2 * i] = fmaf(l0[j - 1], lo, o0[2 * i]); o0[2 * i + 1] = fmaf(l0[j - 1], hi, o0[2 * i + 1]); }
                        if (j < 8) { o1[2 * i] = fmaf(l1[j], lo, o1[2 * i]); o1[2 * i + 1] = fmaf(l1[j], hi, o1[2 * i + 1]); }
                    }
                }
                s0 = 1.f / s0; s1 = 1.f / s1;
                uint2* dst = reinterpret_cast<uint2*>(g_oA + (size_t)t0 * DM + lane * 20);
#pragma unroll
                for (int i = 0; i < 5; i++) {
                    dst[i] = make_uint2(pack2(o0[4 * i] * s0, o0[4 * i + 1] * s0), pack2(o0[4 * i + 2] * s0, o0[4 * i + 3] * s0));
                    dst[i + 2 * DM / 4] = make_uint2(pack2(o1[4 * i] * s1, o1[4 * i + 1] * s1), pack2(o1[4 * i + 2] * s1, o1[4 * i + 3] * s1));
                }
                __syncwarp();
                if (lane == 0) red_release(g_cnt + CNT_ATT + (t0 >> 8), 2);
            }
            int j = 0;
            while ((jobs[j].x & 7) != JEND) j++;
            for (j++; (jobs[j].x & 7) == JR; j++) {
                const Job job = jobs[j];
                const int nb = (job.x >> 3) & 15, ct = (job.x >> 7) & 63;
                for (int c = 0; c < SPIN_LIM && (int)(ld_acquire(g_cnt + CNT_O + (job.y >> 8 & 255) * 5 + ct) - ep * NKS) < 0; c++) __nanosleep(200);
                for (int u = job.y & 15; u < 2 * nb; u += NKS) {
                    const uint4* part = part_ptr(job, warp - 10) + u * 128 + lane;
                    bf16* op = P.out + (size_t)(((job.x >> 13) & 63) * 32 + u * 16 + (lane >> 2)) * OUTW + DM + ct * 128 + (warp - 10) * 64 + (lane & 1) * 8 + (lane & 2) * 2;
#pragma unroll 1
                    for (int h = 0; h < 2; h++) {
                        uint4 q[2][NKS];
#pragma unroll
                        for (int i = 0; i < 2; i++)
#pragma unroll
                            for (int k = 0; k < NKS; k++) q[i][k] = ld_pkt(part + k * nb * 256 + (2 * h + i) * 32);
#pragma unroll
                        for (int i = 0; i < 2; i++) {
                            float r[8] = {0, 0, 0, 0, 0, 0, 0, 0};
#pragma unroll
                            for (int k = 0; k < NKS; k++) {
                                r[0] += bf_lo(q[i][k].x); r[1] += bf_hi(q[i][k].x); r[2] += bf_lo(q[i][k].y); r[3] += bf_hi(q[i][k].y);
                                r[4] += bf_lo(q[i][k].z); r[5] += bf_hi(q[i][k].z); r[6] += bf_lo(q[i][k].w); r[7] += bf_hi(q[i][k].w);
                            }
#pragma unroll
                            for (int m = 0; m < 2; m++) {
                                const uint32_t a = movm(pack2(r[2 * m], r[2 * m + 1])), b = movm(pack2(r[4 + 2 * m], r[5 + 2 * m]));
                                const uint32_t o = __shfl_xor_sync(0xffffffffu, lane & 1 ? a : b, 1);
                                *reinterpret_cast<uint2*>(op + m * 8 * OUTW + (2 * h + i) * 16) = lane & 1 ? make_uint2(o, b) : make_uint2(a, o);
                            }
                        }
                    }
                }
            }
        }
    }
}

typedef CUresult (*EncodeFn)(CUtensorMap*, CUtensorMapDataType, cuuint32_t, void*, const cuuint64_t*, const cuuint64_t*,
                             const cuuint32_t*, const cuuint32_t*, CUtensorMapInterleave, CUtensorMapSwizzle,
                             CUtensorMapL2promotion, CUtensorMapFloatOOBfill);
static void make_map(EncodeFn enc, CUtensorMap* tm, const void* ptr, uint64_t cols, uint64_t rows, uint32_t bc, uint32_t br) {
    cuuint64_t dims[2] = {cols, rows}, strides[1] = {cols * 2};
    cuuint32_t box[2] = {bc, br}, es[2] = {1, 1};
    enc(tm, CU_TENSOR_MAP_DATA_TYPE_BFLOAT16, 2, const_cast<void*>(ptr), dims, strides, box, es, CU_TENSOR_MAP_INTERLEAVE_NONE,
        bc == 64 ? CU_TENSOR_MAP_SWIZZLE_128B : CU_TENSOR_MAP_SWIZZLE_64B,
        CU_TENSOR_MAP_L2_PROMOTION_L2_128B, CU_TENSOR_MAP_FLOAT_OOB_FILL_NONE);
}

static void make_map3(EncodeFn enc, CUtensorMap* tm, const void* ptr, uint64_t cols, uint64_t rows, uint32_t br, uint32_t nb, uint32_t bc = 64) {
    cuuint64_t dims[3] = {bc, rows, cols / bc}, strides[2] = {cols * 2, bc * 2};
    cuuint32_t box[3] = {bc, br, nb}, es[3] = {1, 1, 1};
    enc(tm, CU_TENSOR_MAP_DATA_TYPE_BFLOAT16, 3, const_cast<void*>(ptr), dims, strides, box, es, CU_TENSOR_MAP_INTERLEAVE_NONE,
        bc == 64 ? CU_TENSOR_MAP_SWIZZLE_128B : CU_TENSOR_MAP_SWIZZLE_64B,
        CU_TENSOR_MAP_L2_PROMOTION_L2_128B, CU_TENSOR_MAP_FLOAT_OOB_FILL_NONE);
}

extern "C" void kernel_launch(void* const* d_in, const int* in_sizes, int n_in, void* d_out, int out_size) {
    (void)in_sizes; (void)n_in; (void)out_size;
    const bf16* A_x = (const bf16*)d_in[0];
    const bf16* A_wqkv = (const bf16*)d_in[1];
    const bf16* A_wo = (const bf16*)d_in[2];
    const bf16* B_x = (const bf16*)d_in[3];
    const bf16* B_mem0 = (const bf16*)d_in[4];
    const bf16* B_Wq = (const bf16*)d_in[5];
    const bf16* B_Wk = (const bf16*)d_in[6];
    const bf16* B_Wv = (const bf16*)d_in[7];
    const bf16* B_Wo = (const bf16*)d_in[8];
    bf16* out = (bf16*)d_out;

    static EncodeFn enc = nullptr;
    static void *p_ox, *p_qkv, *p_oA, *p_xch;
    if (!enc) {
        void* fn = nullptr; cudaDriverEntryPointQueryResult qr;
        cudaGetDriverEntryPoint("cuTensorMapEncodeTiled", &fn, cudaEnableDefault, &qr);
        enc = (EncodeFn)fn;
        cudaFuncSetAttribute(chain_kernel, cudaFuncAttributeMaxDynamicSharedMemorySize, CHAIN_SMEM);
        cudaFuncSetAttribute(side_kernel, cudaFuncAttributeMaxDynamicSharedMemorySize, SIDE_SMEM);
        cudaGetSymbolAddress(&p_ox, g_ox); cudaGetSymbolAddress(&p_qkv, g_qkvA); cudaGetSymbolAddress(&p_oA, g_oA);
        cudaGetSymbolAddress(&p_xch, g_xch);
    }
    CUtensorMap tmXA, tmXB, tmWq, tmWk, tmWv, tmWo, tmOx;
    make_map3(enc, &tmXA, B_x, DM, SEQ, 32, NX);
    make_map3(enc, &tmXB, B_x, DM, SEQ, 32, 1);
    make_map(enc, &tmWq, B_Wq, HE, DM, 64, 128);
    make_map(enc, &tmWk, B_Wk, HE, DM, 64, 128);
    make_map(enc, &tmWv, B_Wv, HE, DM, 64, 128);
    make_map3(enc, &tmWo, B_Wo, DM, HE, 64, 7, 32);
    SideParams sp;
    sp.out = out;
    make_map3(enc, &sp.a[JV], B_Wv, HE, DM, 64, 2);
    make_map3(enc, &sp.a[JQ], A_wqkv, 3 * DM, DM, 64, 2);
    make_map3(enc, &sp.a[JP], A_wo, DM, DM, 64, 2);
    make_map3(enc, &sp.a[JO], B_Wo, DM, HE, 64, 2);
    const void* act[4] = {B_x, A_x, p_oA, p_ox};
    for (int i = 0; i < 4; i++) make_map(enc, &sp.b[i], act[i], i == JO ? HE : DM, SEQ, 64, 256);
    make_map(enc, &sp.c[0], B_x, DM, SEQ, 64, 192);
    make_map(enc, &sp.c[1], B_x, DM, SEQ, 64, 128);
    make_map(enc, &sp.c[2], p_ox, HE, SEQ, 64, 128);
    make_map(enc, &sp.c[3], p_ox, HE, SEQ, 64, 64);
    make_map(enc, &tmOx, p_ox, HE, SEQ, 64, 32);
    make_map(enc, &sp.st[0], p_qkv, 3 * DM, SEQ, 64, 256);
    make_map(enc, &sp.st[1], out, OUTW, SEQ, 64, 256);
    make_map(enc, &sp.sto, out, OUTW, SEQ, 64, 16);

    cudaStream_t st = cudaStreamPerThread;
    chain_kernel<<<96, 384, CHAIN_SMEM, st>>>(tmXA, tmXB, tmWq, tmWk, tmWv, tmWo, tmOx, B_mem0, B_x,
                                              (const char*)(((uintptr_t)p_xch + 0x1fffff) & ~(uintptr_t)0x1fffff), out);
    cudaLaunchConfig_t cfg = {};
    cfg.gridDim = dim3(NSIDE); cfg.blockDim = dim3(384); cfg.dynamicSmemBytes = SIDE_SMEM; cfg.stream = st;
    cudaLaunchAttribute at[1];
    at[0].id = cudaLaunchAttributeProgrammaticStreamSerialization; at[0].val.programmaticStreamSerializationAllowed = 1;
    cfg.attrs = at; cfg.numAttrs = 1;
    cudaLaunchKernelEx(&cfg, side_kernel, sp);
}
```

```cpp
#include <cuda_runtime.h>
#include <cuda_bf16.h>
#include <cuda.h>
#include <stdint.h>
#include <string.h>
#include <math.h>
#include <type_traits>

typedef __nv_bfloat16 bf16;

constexpr int SEQ = 2048, DM = 640, NH = 32, DH = 192, HE = NH * DH;
constexpr int NSEG = 64;
constexpr int OUTW = 1280;

__device__ uint4 g_xch[(4 << 20) / 16];
__device__ uint4 g_near4[96 * 4];
__device__ bf16  g_ox[SEQ * HE];
__device__ bf16  g_qkvA[SEQ * 3 * DM];
__device__ bf16  g_oA[SEQ * DM];
__device__ uint4 g_vx[96 * NSEG * 256];
__device__ uint4 g_op[NSEG * 70 * 256];
__device__ uint4 g_tail[2 * 32 * 80 * 32];
__device__ uint32_t g_epoch;
__device__ uint32_t g_flagv[96 * 64];
__device__ uint32_t g_prog[96];
__device__ uint32_t g_cnt[256];
constexpr int CNT_Q = 0, CNT_ATT = 8, CNT_O = 16, SPIN_LIM = 1 << 15;

__device__ __forceinline__ uint32_t smem_u32(const void* p) { return (uint32_t)__cvta_generic_to_shared(p); }
__device__ __forceinline__ uint32_t pack2(float lo, float hi) {
    uint32_t r; asm("cvt.rn.bf16x2.f32 %0, %1, %2;" : "=r"(r) : "f"(hi), "f"(lo)); return r;
}
__device__ __forceinline__ float ex2(float x) { float r; asm("ex2.approx.ftz.f32 %0, %1;" : "=f"(r) : "f"(x)); return r; }
__device__ __forceinline__ float rcpf(float x) { float r; asm("rcp.approx.ftz.f32 %0, %1;" : "=f"(r) : "f"(x)); return r; }
__device__ __forceinline__ void mbar_init(uint32_t bar, uint32_t cnt) {
    asm volatile("mbarrier.init.shared::cta.b64 [%0], %1;" :: "r"(bar), "r"(cnt) : "memory");
}
__device__ __forceinline__ void mbar_arrive(uint32_t bar) {
    asm volatile("mbarrier.arrive.shared::cta.b64 _, [%0];" :: "r"(bar) : "memory");
}
__device__ __forceinline__ void mbar_expect(uint32_t bar, uint32_t bytes) {
    asm volatile("mbarrier.arrive.expect_tx.shared::cta.b64 _, [%0], %1;" :: "r"(bar), "r"(bytes) : "memory");
}
constexpr int WAIT_LIM = 2048;
template <int N> __device__ __forceinline__ void mbar_wait_n(uint32_t bar, uint32_t parity) {
    asm volatile("{.reg .pred p, q; .reg .u32 c; mov.u32 c, %2;\n"
                 "WL_%=: sub.u32 c, c, 1; setp.eq.u32 q, c, 0; @q bra WD_%=; mbarrier.try_wait.parity.shared::cta.b64 p, [%0], %1;\n"
                 "@!p bra WL_%=; WD_%=: }" :: "r"(bar), "r"(parity), "n"(N) : "memory");
}
__device__ __forceinline__ void mbar_wait(uint32_t bar, uint32_t parity) { mbar_wait_n<1024>(bar, parity); }
__device__ __forceinline__ void mbar_wait_long(uint32_t bar, uint32_t parity) { mbar_wait_n<4096>(bar, parity); }
__device__ __forceinline__ void bar_sync(int id, int n) { asm volatile("bar.sync %0, %1;" :: "r"(id), "r"(n) : "memory"); }
__device__ __forceinline__ void bar_arrive(int id, int n) { asm volatile("bar.arrive %0, %1;" :: "r"(id), "r"(n) : "memory"); }
__device__ __forceinline__ void tma2d(uint32_t dst, const CUtensorMap* tm, int c0, int c1, uint32_t bar) {
    asm volatile("cp.async.bulk.tensor.2d.shared::cluster.global.mbarrier::complete_tx::bytes [%0], [%1, {%3, %4}], [%2];"
                 :: "r"(dst), "l"(tm), "r"(bar), "r"(c0), "r"(c1) : "memory");
}
__device__ __forceinline__ void tma_st(const CUtensorMap* tm, uint32_t src, int c0, int c1) {
    asm volatile("cp.async.bulk.tensor.2d.global.shared::cta.bulk_group [%0, {%2, %3}], [%1];" :: "l"(tm), "r"(src), "r"(c0), "r"(c1) : "memory");
}
__device__ __forceinline__ void ldsm4(uint32_t a, uint32_t& r0, uint32_t& r1, uint32_t& r2, uint32_t& r3) {
    asm volatile("ldmatrix.sync.aligned.m8n8.x4.shared.b16 {%0,%1,%2,%3}, [%4];"
                 : "=r"(r0), "=r"(r1), "=r"(r2), "=r"(r3) : "r"(a) : "memory");
}
__device__ __forceinline__ void ldsm4t(uint32_t a, uint32_t& r0, uint32_t& r1, uint32_t& r2, uint32_t& r3) {
    asm volatile("ldmatrix.sync.aligned.m8n8.x4.trans.shared.b16 {%0,%1,%2,%3}, [%4];"
                 : "=r"(r0), "=r"(r1), "=r"(r2), "=r"(r3) : "r"(a) : "memory");
}
__device__ __forceinline__ void ldsm2t(uint32_t a, uint32_t& r0, uint32_t& r1) {
    asm volatile("ldmatrix.sync.aligned.m8n8.x2.trans.shared.b16 {%0,%1}, [%2];" : "=r"(r0), "=r"(r1) : "r"(a) : "memory");
}
__device__ __forceinline__ void stsm4t(uint32_t a, uint32_t r0, uint32_t r1, uint32_t r2, uint32_t r3) {
    asm volatile("stmatrix.sync.aligned.m8n8.x4.trans.shared.b16 [%0], {%1,%2,%3,%4};"
                 :: "r"(a), "r"(r0), "r"(r1), "r"(r2), "r"(r3) : "memory");
}
__device__ __forceinline__ void stsm4(uint32_t a, uint32_t r0, uint32_t r1, uint32_t r2, uint32_t r3) {
    asm volatile("stmatrix.sync.aligned.m8n8.x4.shared.b16 [%0], {%1,%2,%3,%4};"
                 :: "r"(a), "r"(r0), "r"(r1), "r"(r2), "r"(r3) : "memory");
}
__device__ __forceinline__ void stsm2t(uint32_t a, uint32_t r0, uint32_t r1) {
    asm volatile("stmatrix.sync.aligned.m8n8.x2.trans.shared.b16 [%0], {%1,%2};" :: "r"(a), "r"(r0), "r"(r1) : "memory");
}
__device__ __forceinline__ uint32_t movm(uint32_t a) {
    uint32_t d; asm volatile("movmatrix.sync.aligned.m8n8.trans.b16 %0, %1;" : "=r"(d) : "r"(a)); return d;
}
__device__ __forceinline__ void mma16(float* c, uint32_t a0, uint32_t a1, uint32_t a2, uint32_t a3, uint32_t b0, uint32_t b1) {
    asm volatile("mma.sync.aligned.m16n8k16.row.col.f32.bf16.bf16.f32 {%0,%1,%2,%3}, {%4,%5,%6,%7}, {%8,%9}, {%0,%1,%2,%3};"
                 : "+f"(c[0]), "+f"(c[1]), "+f"(c[2]), "+f"(c[3]) : "r"(a0), "r"(a1), "r"(a2), "r"(a3), "r"(b0), "r"(b1));
}
__device__ __forceinline__ void mma8(float* c, uint32_t a0, uint32_t a1, uint32_t b0) {
    asm volatile("mma.sync.aligned.m16n8k8.row.col.f32.bf16.bf16.f32 {%0,%1,%2,%3}, {%4,%5}, {%6}, {%0,%1,%2,%3};"
                 : "+f"(c[0]), "+f"(c[1]), "+f"(c[2]), "+f"(c[3]) : "r"(a0), "r"(a1), "r"(b0));
}
__device__ __forceinline__ void wg_fence() { asm volatile("wgmma.fence.sync.aligned;" ::: "memory"); }
__device__ __forceinline__ void wg_commit() { asm volatile("wgmma.commit_group.sync.aligned;" ::: "memory"); }
template <int N> __device__ __forceinline__ void wg_wait() { asm volatile("wgmma.wait_group.sync.aligned %0;" :: "n"(N) : "memory"); }
__device__ __forceinline__ uint64_t mkdesc(uint32_t addr, uint32_t lbo, uint32_t sbo, uint32_t swz) {
    return (uint64_t)((addr & 0x3FFFF) >> 4) | ((uint64_t)(lbo >> 4) << 16) | ((uint64_t)(sbo >> 4) << 32) | ((uint64_t)swz << 62);
}
template <int BOFF, int SC>
__device__ __forceinline__ void wgmma_rs16(float* d, uint32_t a0, uint32_t a1, uint32_t a2, uint32_t a3, uint32_t blo) {
    asm volatile("{.reg .pred p; .reg .b32 l; .reg .b64 bd; setp.ne.b32 p, %14, 0; add.u32 l, %12, %13; mov.b64 bd, {l, 40};\n"
                 "wgmma.mma_async.sync.aligned.m64n16k16.f32.bf16.bf16 {%0,%1,%2,%3,%4,%5,%6,%7}, {%8,%9,%10,%11}, bd, p, 1, 1, 0;}"
                 : "+f"(d[0]), "+f"(d[1]), "+f"(d[2]), "+f"(d[3]), "+f"(d[4]), "+f"(d[5]), "+f"(d[6]), "+f"(d[7])
                 : "r"(a0), "r"(a1), "r"(a2), "r"(a3), "r"(blo), "n"(BOFF), "n"(SC));
}
template <int BOFF, int SC>
__device__ __forceinline__ void wgmma_rs32n(float* d, uint32_t a0, uint32_t a1, uint32_t a2, uint32_t a3, uint32_t blo) {
    asm volatile("{.reg .pred p; .reg .b32 l; .reg .b64 bd; setp.ne.b32 p, %22, 0; add.u32 l, %20, %21; mov.b64 bd, {l, 40};\n"
                 "wgmma.mma_async.sync.aligned.m64n32k16.f32.bf16.bf16 "
                 "{%0,%1,%2,%3,%4,%5,%6,%7,%8,%9,%10,%11,%12,%13,%14,%15}, {%16,%17,%18,%19}, bd, p, 1, 1, 0;}"
                 : "+f"(d[0]), "+f"(d[1]), "+f"(d[2]), "+f"(d[3]), "+f"(d[4]), "+f"(d[5]), "+f"(d[6]), "+f"(d[7]),
                   "+f"(d[8]), "+f"(d[9]), "+f"(d[10]), "+f"(d[11]), "+f"(d[12]), "+f"(d[13]), "+f"(d[14]), "+f"(d[15])
                 : "r"(a0), "r"(a1), "r"(a2), "r"(a3), "r"(blo), "n"(BOFF), "n"(SC));
}
template <int BOFF, int SC>
__device__ __forceinline__ void wgmma_rs32(float* d, uint32_t a0, uint32_t a1, uint32_t a2, uint32_t a3, uint32_t blo) {
    asm volatile("{.reg .pred p; .reg .b32 l; .reg .b64 bd; setp.ne.b32 p, %22, 0; add.u32 l, %20, %21; mov.b64 bd, {l, 0x40000040};\n"
                 "wgmma.mma_async.sync.aligned.m64n32k16.f32.bf16.bf16 "
                 "{%0,%1,%2,%3,%4,%5,%6,%7,%8,%9,%10,%11,%12,%13,%14,%15}, {%16,%17,%18,%19}, bd, p, 1, 1, 0;}"
                 : "+f"(d[0]), "+f"(d[1]), "+f"(d[2]), "+f"(d[3]), "+f"(d[4]), "+f"(d[5]), "+f"(d[6]), "+f"(d[7]),
                   "+f"(d[8]), "+f"(d[9]), "+f"(d[10]), "+f"(d[11]), "+f"(d[12]), "+f"(d[13]), "+f"(d[14]), "+f"(d[15])
                 : "r"(a0), "r"(a1), "r"(a2), "r"(a3), "r"(blo), "n"(BOFF), "n"(SC));
}
template <int AOFF, int BOFF, int SC>
__device__ __forceinline__ void wgmma_ss32(float* d, uint32_t alo, uint32_t blo) {
    asm volatile("{.reg .pred p; .reg .b32 l, m; .reg .b64 ad, bd; setp.ne.b32 p, %20, 0; add.u32 l, %16, %18; add.u32 m, %17, %19;\n"
                 "mov.b64 ad, {l, 0x40000040}; mov.b64 bd, {m, 0x40000040};\n"
                 "wgmma.mma_async.sync.aligned.m64n32k16.f32.bf16.bf16 "
                 "{%0,%1,%2,%3,%4,%5,%6,%7,%8,%9,%10,%11,%12,%13,%14,%15}, ad, bd, p, 1, 1, 1, 0;}"
                 : "+f"(d[0]), "+f"(d[1]), "+f"(d[2]), "+f"(d[3]), "+f"(d[4]), "+f"(d[5]), "+f"(d[6]), "+f"(d[7]),
                   "+f"(d[8]), "+f"(d[9]), "+f"(d[10]), "+f"(d[11]), "+f"(d[12]), "+f"(d[13]), "+f"(d[14]), "+f"(d[15])
                 : "r"(alo), "r"(blo), "n"(AOFF), "n"(BOFF), "n"(SC));
}
template <int AOFF, int BOFF, int SC>
__device__ __forceinline__ void wgmma_ss8(float* d, uint32_t alo, uint32_t blo) {
    asm volatile("{.reg .pred p; .reg .b32 l, m; .reg .b64 ad, bd; setp.ne.b32 p, %8, 0; add.u32 l, %4, %6; add.u32 m, %5, %7;\n"
                 "mov.b64 ad, {l, 0x40000040}; mov.b64 bd, {m, 0x8};\n"
                 "wgmma.mma_async.sync.aligned.m64n8k16.f32.bf16.bf16 {%0,%1,%2,%3}, ad, bd, p, 1, 1, 1, 1;}"
                 : "+f"(d[0]), "+f"(d[1]), "+f"(d[2]), "+f"(d[3]) : "r"(alo), "r"(blo), "n"(AOFF), "n"(BOFF), "n"(SC));
}
template <int OFF, int SC>
__device__ __forceinline__ void wgmma_ss40(float* d, uint32_t alo, uint32_t blo) {
    asm volatile("{.reg .pred p; .reg .b32 l, m; .reg .b64 ad, bd; setp.ne.b32 p, %23, 0; add.u32 l, %20, %22; add.u32 m, %21, %22;\n"
                 "mov.b64 ad, {l, 0x40000020}; mov.b64 bd, {m, 0x40000040};\n"
                 "wgmma.mma_async.sync.aligned.m64n40k16.f32.bf16.bf16 "
                 "{%0,%1,%2,%3,%4,%5,%6,%7,%8,%9,%10,%11,%12,%13,%14,%15,%16,%17,%18,%19}, ad, bd, p, 1, 1, 0, 0;}"
                 : "+f"(d[0]), "+f"(d[1]), "+f"(d[2]), "+f"(d[3]), "+f"(d[4]), "+f"(d[5]), "+f"(d[6]), "+f"(d[7]),
                   "+f"(d[8]), "+f"(d[9]), "+f"(d[10]), "+f"(d[11]), "+f"(d[12]), "+f"(d[13]), "+f"(d[14]), "+f"(d[15]),
                   "+f"(d[16]), "+f"(d[17]), "+f"(d[18]), "+f"(d[19])
                 : "r"(alo), "r"(blo), "n"(OFF), "n"(SC));
}
template <int I> using IC = std::integral_constant<int, I>;
template <int I, int N, class F> __device__ __forceinline__ void static_for(F&& f) {
    if constexpr (I < N) { f(std::integral_constant<int, I>{}); static_for<I + 1, N>(f); }
}
__device__ __forceinline__ uint32_t mapa(uint32_t a, uint32_t rank) {
    uint32_t r; asm("mapa.shared::cluster.u32 %0, %1, %2;" : "=r"(r) : "r"(a), "r"(rank)); return r;
}
__device__ __forceinline__ void st_async2(uint32_t a, uint32_t x, uint32_t y, uint32_t bar) {
    asm volatile("st.async.weak.shared::cluster.mbarrier::complete_tx::bytes.v2.b32 [%0], {%1,%2}, [%3];"
                 :: "r"(a), "r"(x), "r"(y), "r"(bar) : "memory");
}
__device__ __forceinline__ void st_async1(uint32_t a, uint32_t x, uint32_t bar) {
    asm volatile("st.async.weak.shared::cluster.mbarrier::complete_tx::bytes.b32 [%0], %1, [%2];" :: "r"(a), "r"(x), "r"(bar) : "memory");
}
__device__ __forceinline__ void st_async4(uint32_t a, uint32_t x, uint32_t y, uint32_t z, uint32_t w, uint32_t bar) {
    asm volatile("st.async.weak.shared::cluster.mbarrier::complete_tx::bytes.v4.b32 [%0], {%1,%2,%3,%4}, [%5];"
                 :: "r"(a), "r"(x), "r"(y), "r"(z), "r"(w), "r"(bar) : "memory");
}
__device__ __forceinline__ void sts2(uint32_t a, uint32_t x, uint32_t y) {
    asm volatile("st.shared.v2.b32 [%0], {%1,%2};" :: "r"(a), "r"(x), "r"(y) : "memory");
}
__device__ __forceinline__ void sts4(uint32_t a, uint4 v) {
    asm volatile("st.shared.v4.b32 [%0], {%1,%2,%3,%4};" :: "r"(a), "r"(v.x), "r"(v.y), "r"(v.z), "r"(v.w) : "memory");
}
__device__ __forceinline__ void sts1(uint32_t a, uint32_t x) { asm volatile("st.shared.b32 [%0], %1;" :: "r"(a), "r"(x) : "memory"); }
__device__ __forceinline__ float2 lds2f(uint32_t a) {
    float2 v; asm volatile("ld.shared.v2.f32 {%0,%1}, [%2];" : "=f"(v.x), "=f"(v.y) : "r"(a) : "memory"); return v;
}
__device__ __forceinline__ uint4 lds4(uint32_t a) {
    uint4 v; asm volatile("ld.shared.v4.b32 {%0,%1,%2,%3}, [%4];" : "=r"(v.x), "=r"(v.y), "=r"(v.z), "=r"(v.w) : "r"(a) : "memory"); return v;
}
__device__ __forceinline__ uint32_t lds1(uint32_t a) {
    uint32_t v; asm volatile("ld.shared.b32 %0, [%1];" : "=r"(v) : "r"(a) : "memory"); return v;
}
__device__ __forceinline__ void stg1(void* p, uint32_t x) { asm volatile("st.global.b32 [%0], %1;" :: "l"(p), "r"(x) : "memory"); }
__device__ __forceinline__ uint32_t ld_acquire(const uint32_t* p) {
    uint32_t v; asm volatile("ld.acquire.gpu.global.u32 %0, [%1];" : "=r"(v) : "l"(p) : "memory"); return v;
}
__device__ __forceinline__ uint32_t ld_relaxed(const void* p) {
    uint32_t v; asm volatile("ld.relaxed.gpu.global.u32 %0, [%1];" : "=r"(v) : "l"(p) : "memory"); return v;
}
__device__ __forceinline__ uint32_t ld_epoch() {
    uint32_t v; asm volatile("ld.relaxed.gpu.global.u32 %0, [%1];" : "=r"(v) : "l"(&g_epoch) : "memory"); return v + 1;
}
__device__ __forceinline__ void st_release(uint32_t* p, uint32_t v) { asm volatile("st.release.gpu.global.u32 [%0], %1;" :: "l"(p), "r"(v) : "memory"); }
__device__ __forceinline__ void st_pkt8(const void* p, uint32_t x, uint32_t y) {
    asm volatile("{.reg .b64 v; mov.b64 v, {%1,%2}; st.relaxed.gpu.global.b64 [%0], v;}" :: "l"(p), "r"(x), "r"(y) : "memory");
}
__device__ __forceinline__ void st_pkt4(const void* p, uint32_t x) {
    asm volatile("st.relaxed.gpu.global.b32 [%0], %1;" :: "l"(p), "r"(x) : "memory");
}
__device__ __forceinline__ uint4 ld_pkt(const void* p) {
    uint4 r;
    asm volatile("{.reg .b64 lo, hi; .reg .b128 v; ld.relaxed.gpu.global.b128 v, [%4]; mov.b128 {lo, hi}, v;\n"
                 "mov.b64 {%0,%1}, lo; mov.b64 {%2,%3}, hi;}"
                 : "=r"(r.x), "=r"(r.y), "=r"(r.z), "=r"(r.w) : "l"(p) : "memory");
    return r;
}

template <int OFF> __device__ __forceinline__ void ld_pkt_stale(uint4& r, const void* p, uint32_t tag) {
    asm volatile("{.reg .pred p; .reg .b32 t; .reg .b64 lo, hi; .reg .b128 v; lop3.b32 t, %0, %5, 1, 0x28; setp.ne.u32 p, t, 0;\n"
                 "mov.b64 lo, {%0,%1}; mov.b64 hi, {%2,%3}; mov.b128 v, {lo, hi}; @p ld.relaxed.gpu.global.b128 v, [%4 + %6];\n"
                 "mov.b128 {lo, hi}, v; mov.b64 {%0,%1}, lo; mov.b64 {%2,%3}, hi;}"
                 : "+r"(r.x), "+r"(r.y), "+r"(r.z), "+r"(r.w) : "l"(p), "r"(tag), "n"(OFF) : "memory");
}

constexpr int NX = 7;
constexpr uint32_t OFF_WV = 0, OFF_WO = 81920, OFF_XR = OFF_WO + 86016, OFF_QA = OFF_XR + NX * 4096, OFF_SP = OFF_QA + 5120, OFF_RED = OFF_SP,
                   OFF_BAR = OFF_SP + 2560, OFF_KA = OFF_QA + 8192, OFF_MEMT = OFF_KA + 5120, OFF_SM = OFF_MEMT + 10240, OFF_PM = OFF_SM + 1280,
                   OFF_SX = OFF_PM + 768, OFF_R1 = OFF_SX + 5120, OFF_OX = OFF_R1, OFF_DBG = OFF_R1 + 4096, CHAIN_SMEM = OFF_DBG + 1024,
                   OFF_OXL = OFF_XR, OFF_OXG = OFF_XR + 4096, OFF_R1L = OFF_XR + 20480, OFF_TRED = OFF_WV + 32768;
__host__ __device__ constexpr uint32_t xblk(int kb) { return kb < 3 ? OFF_MEMT - OFF_XR + kb * 4096 : (kb - 3) * 4096; }
constexpr uint32_t MB_S = OFF_BAR, MB_SX = OFF_BAR + 8, MB_O = OFF_BAR + 16, MB_WO = OFF_BAR + 24, MB_XA = OFF_BAR + 32, MB_XB = OFF_BAR + 40,
                   MB_M = OFF_BAR + 48, MB_EM = OFF_BAR + 88, MB_EA = OFF_BAR + 96, OFF_EP = OFF_BAR + 112,
                   MB_F = OFF_BAR + 128, MB_E = OFF_BAR + 168, OFF_ROLE = OFF_BAR + 224, OFF_T = OFF_BAR + 232, OFF_SPO = OFF_BAR + 236, MB_M2 = OFF_BAR + 240;
constexpr int BAR_QM = 0, BAR_PUB = 1, BAR_QK = 2, BAR_P = 3, BAR_WO = 4, BAR_S = 5, BAR_O2 = 6, BAR_O = 7, BAR_R = 8, BAR_PM = 9, BAR_G = 10,
              BAR_X = 15, BAR_R1 = 15, BAR_MEM = 11;
constexpr float SCL_B = 0.07216878364870322f * 1.4426950408889634f;
#define NPROBE 3
#define G1 1056
#define G2 1536
#define F1 0
#define F2 4
#define BN 8
#define BD 1
#define NVR 4
#define NVP 6
#define NVE 6
#define NPF 12
#define NPE 1
#define NPM 7
#define PFV 1
#define PROG 0x5111010101010100ull
#define LEAD 2
#define NV0 3
#define HV 3
#define REL 2
#define RB 1
#define TXD 0
#define TXE 0
#define WOK 0x888
#define AJ 2
#define KJ 9
#define XG 1
#define VFLAGS 0x101010101010444ull
#define SD 0
#define NO2 6
#define OE 0
#define DN 17
#define NOB 2
#define PW0 7
#define PW1 4
#define NVC 2
#define PWIN 2
#define NCP 1

static_assert(PWIN <= 2, "the third piece of the weights is requested behind the store of the epoch, which orders its first use");
static_assert((VFLAGS & ((4ull << NVC) - 1)) == 1ull << NVC, "first block of v");
__device__ __forceinline__ uint32_t clk32() { uint32_t c; asm volatile("mov.u32 %0, %%clock;" : "=r"(c)); return c; }
__device__ __forceinline__ void spin(uint32_t n) { const uint32_t t = clk32(); while (clk32() - t < n) { } }
__device__ __forceinline__ uint32_t gtime() { uint32_t c; asm volatile("mov.u32 %0, %%globaltimer_lo;" : "=r"(c)); return c; }
__device__ __forceinline__ void ggate(uint32_t t) { while ((int)(gtime() - t) < 0) { } }
template <int N> __device__ __forceinline__ void pause() {
    if constexpr (N > 0) {
        uint32_t x = clk32();
#pragma unroll
        for (int i = 1; i < N; i++) asm volatile("mad.lo.u32 %0, %0, %0, %0;" : "+r"(x));
        asm volatile("{.reg .pred p; .reg .b32 t; mad.lo.u32 t, %0, %0, %0; setp.eq.u32 p, t, 1; @p exit;}" :: "r"(x) : "memory");
    }
}
__device__ __forceinline__ uint32_t laneid() { uint32_t c; asm volatile("mov.u32 %0, %%laneid;" : "=r"(c)); return c; }
template <int K> __device__ __forceinline__ uint32_t opq0(uint32_t s) { uint32_t c; asm volatile("shr.u32 %0, %1, %2;" : "=r"(c) : "r"(s), "n"(K)); return c; }
__device__ __forceinline__ uint32_t keep(uint32_t x) { asm volatile("" : "+r"(x)); return x; }
template <class T> __device__ __forceinline__ T* keepp(T* p) { asm volatile("" : "+l"(p)); return p; }
__device__ __forceinline__ void sched() { asm volatile("bar.warp.sync 0xffffffff;" ::: "memory"); }
__device__ __forceinline__ void blk(int s) { asm volatile("{.reg .pred p; setp.gt.s32 p, %0, 1000; @p exit;}" :: "r"(s) : "memory"); }
__device__ __forceinline__ uint32_t selu(bool c, uint32_t a, uint32_t b) {
    uint32_t r; asm("{.reg .pred p; setp.ne.u32 p, %1, 0; selp.b32 %0, %2, %3, p;}" : "=r"(r) : "r"((uint32_t)c), "r"(a), "r"(b)); return r;
}
__device__ __forceinline__ float bf_lo(uint32_t w) { return __uint_as_float(w << 16); }
__device__ __forceinline__ float bf_hi(uint32_t w) { return __uint_as_float(w & 0xffff0000u); }
__device__ __forceinline__ uint32_t badd2(uint32_t a, uint32_t b) { uint32_t r; asm("add.rn.bf16x2 %0, %1, %2;" : "=r"(r) : "r"(a), "r"(b)); return r; }
__device__ __forceinline__ uint32_t tagx(uint32_t a, uint32_t b, uint32_t t) { uint32_t r; asm("lop3.b32 %0, %1, %2, %3, 0x7e;" : "=r"(r) : "r"(a), "r"(t), "r"(b)); return r; }
__device__ __forceinline__ uint32_t tagv(uint32_t a, uint32_t b, uint32_t t) { uint32_t r; asm volatile("lop3.b32 %0, %1, %2, %3, 0x7e;" : "=r"(r) : "r"(a), "r"(t), "r"(b)); return r; }
__device__ __forceinline__ uint32_t or3(uint32_t a, uint32_t b, uint32_t c) { uint32_t r; asm("lop3.b32 %0, %1, %2, %3, 0xfe;" : "=r"(r) : "r"(a), "r"(b), "r"(c)); return r; }
__device__ __forceinline__ bool any_bit0(uint32_t a, uint32_t b) {
    uint32_t r;
    asm volatile("{.reg .pred p; .reg .b32 t; lop3.b32 t, %1, 1, %2, 0xc8; setp.ne.u32 p, t, 0; vote.sync.any.pred p, p, 0xffffffff; selp.u32 %0, 1, 0, p;}"
                 : "=r"(r) : "r"(a), "r"(b));
    return r;
}
__device__ __forceinline__ void arrive_e(uint32_t bar) {
    asm volatile("{.reg .pred p; elect.sync _|p, 0xffffffff; @p mbarrier.arrive.shared::cta.b64 _, [%0];}" :: "r"(bar) : "memory");
}
__device__ __forceinline__ void expect_e(uint32_t bar, uint32_t bytes) {
    asm volatile("{.reg .pred p; elect.sync _|p, 0xffffffff; @p mbarrier.arrive.expect_tx.shared::cta.b64 _, [%0], %1;}" :: "r"(bar), "r"(bytes) : "memory");
}
__device__ __forceinline__ void tma2d_e(uint32_t dst, const CUtensorMap* tm, int c0, int c1, uint32_t bar) {
    asm volatile("{.reg .pred p; elect.sync _|p, 0xffffffff;\n"
                 "@p cp.async.bulk.tensor.2d.shared::cluster.global.mbarrier::complete_tx::bytes [%0], [%1, {%3, %4}], [%2];}"
                 :: "r"(dst), "l"(tm), "r"(bar), "r"(c0), "r"(c1) : "memory");
}
__device__ __forceinline__ void ldsm4_if(bool c, uint32_t a, uint32_t& r0, uint32_t& r1, uint32_t& r2, uint32_t& r3) {
    asm volatile("{.reg .pred p; setp.ne.u32 p, %5, 0; @p ldmatrix.sync.aligned.m8n8.x4.shared.b16 {%0,%1,%2,%3}, [%4];}"
                 : "+r"(r0), "+r"(r1), "+r"(r2), "+r"(r3) : "r"(a), "r"((uint32_t)c) : "memory");
}
__device__ __forceinline__ bool arrive_unless(uint32_t a, uint32_t m, int bar, int n) {
    uint32_t r;
    asm volatile("{.reg .pred p; .reg .b32 t; and.b32 t, %1, %2; setp.ne.u32 p, t, 0; vote.sync.any.pred p, p, 0xffffffff; @!p bar.arrive %3, %4;"
                 " selp.u32 %0, 1, 0, p;}" : "=r"(r) : "r"(a), "r"(m), "r"(bar), "r"(n) : "memory");
    return r;
}
__device__ __forceinline__ bool sync_unless(uint32_t a, uint32_t b, uint32_t m, int bar, int n) {
    uint32_t r;
    asm volatile("{.reg .pred p; .reg .b32 t; lop3.b32 t, %1, %2, %3, 0xa8; setp.ne.u32 p, t, 0; vote.sync.any.pred p, p, 0xffffffff; @!p bar.sync %4, %5;"
                 " selp.u32 %0, 1, 0, p;}" : "=r"(r) : "r"(a), "r"(b), "r"(m), "n"(BAR_R), "n"(128) : "memory");
    return r;
}
__device__ __forceinline__ uint32_t pack2v(float lo, float hi) {
    uint32_t r; asm volatile("cvt.rn.bf16x2.f32 %0, %1, %2;" : "=r"(r) : "f"(hi), "f"(lo)); return r;
}
__device__ __forceinline__ void st_pkt(const void* p, uint4 v) {
    asm volatile("{.reg .b64 lo, hi; .reg .b128 v; mov.b64 lo, {%1,%2}; mov.b64 hi, {%3,%4}; mov.b128 v, {lo, hi}; st.relaxed.gpu.global.b128 [%0], v;}"
                 :: "l"(p), "r"(v.x), "r"(v.y), "r"(v.z), "r"(v.w) : "memory");
}
__device__ __forceinline__ void bulk_ld_e(uint32_t dst, const void* src, uint32_t bytes, uint32_t bar) {
    asm volatile("{.reg .pred p; elect.sync _|p, 0xffffffff;\n"
                 "@p cp.async.bulk.shared::cluster.global.mbarrier::complete_tx::bytes [%0], [%1], %2, [%3];}"
                 :: "r"(dst), "l"(src), "r"(bytes), "r"(bar) : "memory");
}
template <int OFF> __device__ __forceinline__ void ld_pkt8(uint32_t& x, uint32_t& y, const void* p) {
    asm volatile("{.reg .b64 v; ld.relaxed.gpu.global.b64 v, [%2 + %3]; mov.b64 {%0,%1}, v;}" : "=r"(x), "=r"(y) : "l"(p), "n"(OFF) : "memory");
}
__device__ __forceinline__ void tma3d_e(uint32_t dst, const CUtensorMap* tm, int c1, int c2, uint32_t bar) {
    asm volatile("{.reg .pred p; elect.sync _|p, 0xffffffff;\n"
                 "@p cp.async.bulk.tensor.3d.shared::cluster.global.mbarrier::complete_tx::bytes [%0], [%1, {0, %3, %4}], [%2];}"
                 :: "r"(dst), "l"(tm), "r"(bar), "r"(c1), "r"(c2) : "memory");
}

constexpr uint32_t XCH_PART = 0x80000;
__device__ __forceinline__ uint32_t xch_line(uint32_t r) { return r ^ ((1 ^ r >> 1 ^ r >> 4 ^ r >> 5) & 1); }
__host__ __device__ constexpr uint32_t xch_mem(uint32_t cg) { return 0x48000 + (cg & 1) * 0x4000 + (cg >> 1) * 0x100000; }
__host__ __device__ constexpr uint32_t xch_copy(uint32_t k) { return (0x22123000u >> 8 * k & 255) << 12; }
__device__ __forceinline__ uint32_t mem_row(uint32_t c) { return (c & 16) * 16 + (c & 4) * 32 + ((((c >> 1) ^ c) & 4) | (c & 3)) * 16; }

#define BORD 0xcb43a29180ull
__host__ __device__ constexpr int bulk_ord(int h) { return (BORD >> 4 * h) & 15; }
__host__ __device__ constexpr int bulk_pos(int k) {
    int r = -1;
    for (int h = 0; h < 10; h++) {
        const int v = bulk_ord(h);
        if ((k == 0 ? (v & 7) == 2 : k == 3 ? (v & 7) < 3 : (v >> 3) == (k == 2)) && (k >= 3 || r < 0)) r = h;
    }
    return r;
}

__device__ __forceinline__ void set_role(uint32_t sb, uint32_t r) {
    const uint32_t role = xch_line(r);
    sts1(sb + OFF_ROLE, role | (xch_mem((role & 255) / 20) + ((role & 255) % 20) * 128) << 2);
    sts1(sb + OFF_SPO, 0x44000 + xch_copy(1 + (role >> 1 & 1)) + (role >> 8) * 4096);
}
__device__ __forceinline__ void pick_role(uint32_t sb, bool second, uint32_t page, const char* pp, uint32_t ep) {
    uint32_t* const g_near = reinterpret_cast<uint32_t*>(g_near4);
    const uint32_t ln = laneid();
    if (!second) {
        if (ln == 0) {
            uint32_t t = 4095;
#pragma unroll 1
            for (int i = 0; i < NPROBE; i++) {
                const uint32_t c0 = clk32();
                uint32_t c1 = c0 - 1;
                asm volatile("{.reg .pred p; .reg .b32 x; atom.relaxed.gpu.global.exch.b32 x, [%1], %2; setp.le.u32 p, x, %2; @p mov.u32 %0, %%clock;}"
                             : "+r"(c1) : "l"(pp + page * 4096), "r"(i) : "memory");
                t = min(t, c1 - c0);
            }
            asm volatile("st.relaxed.gpu.global.v4.b32 [%0], {%1,%1,%1,%1}; st.relaxed.gpu.global.v4.b32 [%0 + 16], {%1,%1,%1,%1};"
                         :: "l"(g_near + blockIdx.x * 16 + page * 8), "r"(ep << 12 | t) : "memory");
        }
        __syncwarp();
    } else {
        int d = 0;
#pragma unroll 1
        for (int c = 0; c < SPIN_LIM; c++) {
            uint32_t bad = 0;
            d = 0;
#pragma unroll
            for (int i = 0; i < 6; i++) { const uint32_t a = ld_relaxed(g_near + ln * 48 + i * 8); bad |= a ^ ep << 12; d += i & 1 ? -(int)a : (int)a; }
            if (__all_sync(0xffffffffu, bad < 4096)) break;
            __nanosleep(100);
        }
        const uint32_t bm = __ballot_sync(0xffffffffu, d > 0), cl = blockIdx.x / 3;
        const uint32_t side = bm >> cl & 1;
        const int n1 = 3 * __popc(bm), r1 = 3 * __popc(bm & ((1u << cl) - 1));
        const int rk = side ? r1 + blockIdx.x % 3 : blockIdx.x - r1, no = side ? 96 - n1 : n1;
        const uint32_t next = side << 8 | (rk < 40 ? 2 * rk + side : min(2 * (no + rk - 40) + (side ^ 1), 95));
        set_role(sb, next);
    }
}

__host__ __device__ constexpr int out_ord(int n) {
    return n < 8 ? n : n < 8 + LEAD ? 2 * (n - 4) : n >= 24 - LEAD ? 2 * (n - 12) + 1 : (n - LEAD) & 1 ? n - LEAD : n + LEAD;
}
__device__ __forceinline__ void share_o(uint32_t sb, uint32_t rank, uint32_t src, uint32_t t) {
#pragma unroll
    for (uint32_t p = 1; p < 3; p++) {
        const uint32_t pb = mapa(sb, (rank + p) % 3);
        asm volatile("{.reg .pred p; elect.sync _|p, 0xffffffff;\n"
                     "@p cp.async.bulk.shared::cluster.shared::cta.mbarrier::complete_tx::bytes [%0], [%1], 4096, [%2];}"
                     :: "r"(pb + OFF_OXG + t * 8192 + (2 - p) * 4096), "r"(sb + src), "r"(pb + MB_F + 8 * t) : "memory");
    }
}

#define LANE_REGS const uint32_t l16 = __shfl_sync(0xffffffffu, sb + (tid & 31) * 16, tid & 31); const int lane = (l16 - sb) >> 4

__global__ void __cluster_dims__(3, 1, 1) __launch_bounds__(384, 1)
chain_kernel(const __grid_constant__ CUtensorMap tmXA, const __grid_constant__ CUtensorMap tmXB, const __grid_constant__ CUtensorMap tmWq, const __grid_constant__ CUtensorMap tmWk,
             const __grid_constant__ CUtensorMap tmWv, const __grid_constant__ CUtensorMap tmWo,
             const __grid_constant__ CUtensorMap tmOx, const bf16* __restrict__ mem0,
             const char* win,
             bf16* out)
{
    extern __shared__ __align__(1024) uint8_t smem[];
    const uint32_t sb = smem_u32(smem);
    const int tid = threadIdx.x;
    const int warp = __shfl_sync(0xffffffffu, tid >> 5, 0);
    uint32_t rank; asm("mov.u32 %0, %%cluster_ctarank;" : "=r"(rank));
    const int head = blockIdx.x / 3;
    if (tid == 256) {
#pragma unroll
        for (int i = 0; i < PWIN; i++) mbar_init(sb + MB_F + 8 * i, 1);
        asm volatile("fence.proxy.async.shared::cta;" ::: "memory");
#pragma unroll
        for (int i = 0; i < PWIN; i++) {
            tma2d(sb + OFF_WV + i * 16384, &tmWq, blockIdx.x * 64, i * 128, sb + MB_F + 8 * i);
            tma2d(sb + OFF_WO + i * 16384, &tmWk, blockIdx.x * 64, i * 128, sb + MB_F + 8 * i);
            mbar_expect(sb + MB_F + 8 * i, 32768);
        }
    }
    if (tid == 288) {
        mbar_init(sb + MB_XA, 2); mbar_init(sb + MB_XB, 1);
        mbar_init(sb + MB_S, 5); mbar_init(sb + MB_SX, 1); mbar_init(sb + MB_O, 1); mbar_init(sb + MB_WO, 1);
        for (int i = 0; i < 4; i++) { mbar_init(sb + MB_M + 8 * i, 1); mbar_init(sb + MB_M2 + 8 * i, 1); }
        mbar_init(sb + MB_EM, 4); mbar_init(sb + MB_EA, 8);
        for (int i = 0; i < 5; i++) { if (i >= PWIN) mbar_init(sb + MB_F + 8 * i, 1); mbar_init(sb + MB_E + 8 * i, 8); }
        asm volatile("fence.mbarrier_init.release.cluster;" ::: "memory");
        asm volatile("fence.proxy.async.shared::cta;" ::: "memory");
        mbar_expect(sb + MB_XA, NX * 4096); mbar_expect(sb + MB_XA, 8192); mbar_expect(sb + MB_XB, 4096);
        asm volatile("cp.async.bulk.tensor.3d.shared::cluster.global.mbarrier::complete_tx::bytes [%0], [%1, {0, 0, 3}], [%2];"
                     :: "r"(sb + OFF_XR), "l"(&tmXA), "r"(sb + MB_XA) : "memory");
        for (int i = 0; i < 3; i++)
            asm volatile("cp.async.bulk.tensor.3d.shared::cluster.global.mbarrier::complete_tx::bytes [%0], [%1, {0, 0, %3}], [%2];"
                         :: "r"(sb + OFF_MEMT + i * 4096), "l"(&tmXB), "r"(sb + (i < 2 ? MB_XA : MB_XB)), "r"(i) : "memory");
        mbar_expect(sb + MB_WO, 86016);
    }
    __syncwarp();
    const char* pp = win + 0x44000 + (blockIdx.x & 63) * 64 + (blockIdx.x >> 6) * 0x100000;
    if (warp >= 10 && (tid & 31) < 8) st_pkt4(pp + (warp & 1) * 4096 + (tid & 7) * 4, 0);
    const uint32_t ep0 = ld_relaxed(&g_epoch);
    if (tid >= 160 && tid < 240) asm volatile("prefetch.global.L2 [%0];" :: "l"(mem0 + (tid - 160) * 64));
    if (tid >= 64 && tid < 67) asm volatile("prefetch.tensormap [%0];" :: "l"(tid == 64 ? &tmWv : tid == 65 ? &tmWo : &tmOx) : "memory");
    asm volatile("griddepcontrol.launch_dependents;" ::: "memory");
    __syncthreads();
    asm volatile("barrier.cluster.arrive.release.aligned;" ::: "memory");

    if (warp < 8) {
        asm volatile("setmaxnreg.inc.sync.aligned.u32 224;");
        LANE_REGS;
        const int w4 = warp & 3;
        const uint32_t st0 = __shfl_sync(0xffffffffu, sb + (warp >> 2) * 8192 + ((lane & 7) + ((lane >> 4) << 3)) * 128 +
                                                      (((2 * w4 + ((lane >> 3) & 1)) ^ (lane & 7)) << 4), lane);
        const uint32_t st_addr = st0 + OFF_QA;
        const uint32_t xr_lo = (((sb + OFF_XR) & 0x3FFFF) >> 4) | (1u << 16);
        const uint32_t p1 = mapa(sb, (rank + 1) % 3), p2 = mapa(sb, (rank + 2) % 3), p1s = p1 - sb + OFF_SP, p2s = p2 - sb + OFF_SP + 1280;
        const uint32_t box = rank * 7 + warp;
        const bool act = warp < 7 && box < 20;
        const uint32_t gp = XCH_PART + box * 0x4000 + head * 128;
        const int wg = __reduce_max_sync(0xffffffffu, (unsigned)tid >> 7);
        const uint32_t vo = __reduce_max_sync(0xffffffffu, ((unsigned)tid >> 7) * 32768);
        const uint32_t mo = __reduce_max_sync(0xffffffffu, ((unsigned)tid >> 7) * 5120);
        const uint32_t xa_lo = xr_lo + wg * 5 * 256, xb_lo = xr_lo + xblk(0) / 16 + wg * (2 * 256 - xblk(0) / 16);
        uint32_t wa[80], wb[80];
        {
            const uint32_t src = st_addr - OFF_QA + wg * (40960 - 8192);
            if (wg) { arrive_e(sb + MB_E); arrive_e(sb + MB_E + 8); } else { arrive_e(sb + MB_E + 24); arrive_e(sb + MB_E + 32); }
#pragma unroll
            for (int k = 0; k < 20; k++) {
                if (k % 4 == 0) mbar_wait(sb + MB_F + ((wg * 20 + k) >> 3) * 8, 0);
                ldsm4t(src + wg * OFF_WO + k * 2048, wa[4 * k], wa[4 * k + 1], wa[4 * k + 2], wa[4 * k + 3]);
                ldsm4t(src + (wg ^ 1) * OFF_WO + k * 2048, wb[4 * k], wb[4 * k + 1], wb[4 * k + 2], wb[4 * k + 3]);
                if (k % 4 == 3 && (k == 19 || (k & 4) >> 2 != wg)) arrive_e(sb + MB_E + ((wg * 20 + k) >> 3) * 8);
            }
        }
        asm volatile("barrier.cluster.wait.acquire.aligned;" ::: "memory");
        mbar_wait(sb + MB_XA, 0);
        const uint32_t lb = __shfl_sync(0xffffffffu, sb + mem_row(tid & 31), tid & 31);

        for (int s = 0; ; s++) {
            uint32_t b[10][4], v[20][4];
            auto ldv = [&](int n) { ldsm4t(st0 + vo + (OFF_WV + n * 2048), v[n][0], v[n][1], v[n][2], v[n][3]); };
            auto ldb = [&](int j) { ldsm4t(lb + mo + (OFF_MEMT + j * 512), b[j][0], b[j][1], b[j][2], b[j][3]); };
#pragma unroll
            for (int n = 0; n < NV0; n++) ldv(n);
            if (s > 0) bar_sync(BAR_WO, 384);
            {
                float pa[16], acc[16];
#pragma unroll
                for (int i = 0; i < 16; i++) pa[i] = acc[i] = 0.f;
                static_for<0, 10>([&](auto H) {
                    constexpr int h = H.value, kb = bulk_ord(h) & 7, own = bulk_ord(h) >> 3;
                    if constexpr (h == bulk_pos(0)) { if (!wg) mbar_wait(sb + MB_XB, s & 1); }
                    if constexpr (h == PW0 && h == bulk_pos(3) + 1) { if (!wg) { wg_wait<0>(); arrive_e(sb + MB_EM); } }
                    if constexpr (h == PW0 || h == PW1) { if (s >= NVC && (PW0 == PW1 || (h == PW0 ? !wg : wg))) { bar_sync(BAR_PUB, 288); } }
                    if (h == 0 || h == bulk_pos(3) + 1 + (PW0 != bulk_pos(3) + 1) || h == bulk_pos(4) + 2 || h == bulk_pos(0)) wg_fence();
                    static_for<0, 4>([&](auto K4) {
                        constexpr int k4 = K4.value, r = 16 * kb + 4 * k4;
                        const uint32_t* w = own ? wa : wb;
                        wgmma_rs32<(kb < 3 ? kb : kb - 3) * 256 + k4 * 2, k4 != 0 || h != bulk_pos(1 + own)>(own ? acc : pa, w[r], w[r + 1], w[r + 2], w[r + 3], kb < 3 ? xb_lo : xa_lo);
                    });
                    wg_commit();
                    if constexpr (h == HV) {
#pragma unroll
                        for (int n = NV0; n < NVE; n++) ldv(n);
                    }
                    if constexpr (h != PW0 && h == bulk_pos(3) + 1) { if (!wg) { wg_wait<1>(); arrive_e(sb + MB_EM); } }
                    if constexpr (h == bulk_pos(4) + 1) {
                        const uint32_t st_oth = keep((((st0 ^ opq0<8>(s)) - sb) ^ 8192) + sb) + OFF_QA;
                        wg_wait<1>();
                        stsm4t(st_oth + 1024, pack2(pa[0], pa[1]), pack2(pa[2], pa[3]), pack2(pa[4], pa[5]), pack2(pa[6], pa[7]));
                        stsm4t(st_oth + 3072, pack2(pa[8], pa[9]), pack2(pa[10], pa[11]), pack2(pa[12], pa[13]), pack2(pa[14], pa[15]));
                    }
                });
                if (s == 0) {
                    if (warp == 2) pick_role(sb, true, 0, pp, lds1(sb + OFF_EP));
#pragma unroll 1
                    for (int i = warp >> 1 & 2; i < (warp >> 1 & 2) + 3; i++) { mbar_wait_long(sb + MB_E + 8 * i, 0); mbar_wait_long(sb + MB_F + 8 * i, 1); }
#pragma unroll
                    for (int n = 0; n < NVE; n++) ldv(n);
                }
                bar_sync(BAR_QK, 256);
                uint32_t u[8];
                ldsm4t(st_addr + 1024, u[0], u[1], u[2], u[3]);
                ldsm4t(st_addr + 3072, u[4], u[5], u[6], u[7]);
#pragma unroll
                for (int n = NVE; n < NVP; n++) ldv(n);
                wg_wait<0>();
                arrive_e(sb + MB_EA);
#pragma unroll
                for (int i = 0; i < 8; i++) u[i] = badd2(u[i], pack2(acc[2 * i], acc[2 * i + 1]));
                stsm4t(st_addr + 1024, u[0], u[1], u[2], u[3]);
                stsm4t(st_addr + 3072, u[4], u[5], u[6], u[7]);
                if (RB && wg) bar_arrive(BAR_R1, 288);
            }
            uint32_t lo = 0, so = 0, a[16], kb[8], k1[8];
            const uint32_t r1 = s == NSEG - 1 ? OFF_R1L : OFF_R1;
            float cv[4] = {0, 0, 0, 0};
            {
                float ca[4] = {0, 0, 0, 0}, cb[4] = {0, 0, 0, 0};
                uint32_t sq = 0, ln = 0, lq = 0, lk = 0;
                blk(warp);
                if (wg) bar_sync(BAR_MEM + 2, 160); else bar_sync(BAR_MEM, 160);
                int nb = 0, nv = NVP;
                for (; nb < BD; nb++) ldb(nb);
#pragma unroll
                for (int j = 0; j < 10; j++) {
                    if (2 * j == BN) { if (wg) bar_sync(BAR_MEM + 3, 160); else bar_sync(BAR_MEM + 1, 160); }
                    for (; nb <= j + BD && nb < (2 * j >= BN ? 10 : 5); nb++) ldb(nb);
                    if (j == KJ) {
                        if (!RB) bar_sync(BAR_R1, 288); else if (wg) bar_sync(BAR_PM, 160); else bar_sync(BAR_R1, 288);
#pragma unroll
                        for (int i = 0; i < 4; i++) { kb[i] = b[KJ - 2][i]; kb[4 + i] = b[KJ - 1][i]; }
                        ldsm4_if((uint32_t)(warp - 1) < 4, OFF_KA + lo, kb[0], kb[1], kb[2], kb[3]);
                        ldsm4_if((uint32_t)(warp - 1) < 4, OFF_KA + (lo ^ 64), kb[4], kb[5], kb[6], kb[7]);
                    }
                    blk(warp);
#pragma unroll
                    for (int i = 0; i < 2; i++) {
                        const int n = 2 * j + i;
                        if (i && n == BN) {
                            if (wg) bar_sync(BAR_MEM + 3, 160); else bar_sync(BAR_MEM + 1, 160);
                            for (; nb <= j + BD; nb++) ldb(nb);
                            blk(warp);
                        }
                        mma16(cb, wb[4 * n], wb[4 * n + 1], wb[4 * n + 2], wb[4 * n + 3], b[j][2 * i], b[j][2 * i + 1]);
                        mma16(ca, wa[4 * n], wa[4 * n + 1], wa[4 * n + 2], wa[4 * n + 3], b[j][2 * i], b[j][2 * i + 1]);
                        mma16(cv, v[n][0], v[n][1], v[n][2], v[n][3], b[j][2 * i], b[j][2 * i + 1]);
                        if (n >= NVP - NVR && nv < 20) ldv(nv++);
                    }
                    if (j == AJ) { const uint32_t o = (st0 ^ opq0<9>(s)) - sb; ln = keep((o >> 7 & 7) | ((o ^ o >> 3) >> 1 & 8) | (o >> 6 & 16)); }
                    if (j == AJ + 1) lo = keep(sb + (ln & 7) * 128 + (((ln >> 3) ^ (ln & 7)) << 4) + warp * 1024);
                    if (j == AJ + 2) {
                        lk = keep(sb + ln * 16);
                        sq = keep((lk & ~256u) + (warp & 3) * 256 + selu((ln >> 4) == warp >> 2, r1 + (warp >> 2) * 1024, OFF_KA - (warp >> 2) * 8192));
                    }
                    if (j == AJ + 3) so = keep(sb + warp * 256 + ((ln * 8) ^ (warp & 3) * 32));
                    if (j == AJ + 4) lq = keep(sb + r1 + (ln & 8) * 128 + (ln >> 4) * 128 + (ln & 7) * 16);
                    if (j == AJ + 5) {
#pragma unroll
                        for (int i = 0; i < 8; i++) k1[i] = opq0<11>(s);
                    }
                }
                a[0] = pack2(ca[0], ca[1]); a[1] = pack2(ca[2], ca[3]); a[2] = pack2(cb[0], cb[1]); a[3] = pack2(cb[2], cb[3]);
                stsm4t(sq, a[0], a[1], a[2], a[3]);
                sts2(so + r1 + 2048, pack2(cv[0], cv[1]), pack2(cv[2], cv[3]));
                bar_sync(BAR_QM, 256);
#pragma unroll
                for (int i = 0; i < 4; i++) { a[4 + i] = __float_as_uint(ca[i]); a[8 + i] = __float_as_uint(cb[i]); a[12 + i] = b[9][i]; }
                ldsm4_if(warp < 5, lq, a[0], a[1], a[2], a[3]);
                ldsm4_if(warp == 0, lk + OFF_KA, kb[0], kb[1], kb[2], kb[3]);
                ldsm4_if(warp < 5, lq + 256, a[4], a[5], a[6], a[7]);
                ldsm4_if(warp == 0, lk + OFF_QA, k1[0], k1[1], k1[2], k1[3]);
                ldsm4_if(warp < 5, lq + 512, a[8], a[9], a[10], a[11]);
                ldsm4_if(warp == 0, lk + OFF_KA + 512, kb[4], kb[5], kb[6], kb[7]);
                ldsm4_if(warp < 5, lq + 768, a[12], a[13], a[14], a[15]);
                ldsm4_if(warp == 0, lk + OFF_QA + 512, k1[4], k1[5], k1[6], k1[7]);
            }
            if (__builtin_expect(warp < 5, 1)) {
                const uint32_t r1a = keep(p1s + so), r2a = keep(p2s + so), m1 = keep(p1 + MB_S), m2 = keep(p2 + MB_S);
                blk(warp);
#pragma unroll
                for (int i = 0; i < 8; i++) kb[i] = badd2(kb[i], k1[i]);
                float d[4][4];
#pragma unroll
                for (int i = 0; i < 4; i++) {
                    d[i][0] = d[i][1] = d[i][2] = d[i][3] = 0.f;
                    mma16(d[i], a[4 * i], a[4 * i + 1], a[4 * i + 2], a[4 * i + 3], kb[2 * i], kb[2 * i + 1]);
                }
                const uint32_t x = __float_as_uint((((d[0][0] + d[0][2]) + (d[1][0] + d[1][2])) + (d[2][0] + d[2][2])) + (d[3][0] + d[3][2]));
                const uint32_t y = __float_as_uint((((d[0][1] + d[0][3]) + (d[1][1] + d[1][3])) + (d[2][1] + d[2][3])) + (d[3][1] + d[3][3]));
                st_async2(r1a, x, y, m1);
                st_async2(r2a, x, y, m2);
                sts2(so + OFF_SM, x, y);
                __syncwarp();
                expect_e(sb + MB_S, 512);
                if (warp == 0) { stsm4(OFF_KA + lo, kb[0], kb[1], kb[2], kb[3]); stsm4(OFF_KA + (lo ^ 64), kb[4], kb[5], kb[6], kb[7]); }
                bar_arrive(BAR_S, 288); bar_arrive(BAR_O2, 256);
            } else {
                if (warp == 7 && s < NSEG - 1) {
                    pause<SD>();
                    const uint32_t now = gtime() & ~31u, ln = laneid(), sq = (s - lds1(sb + OFF_EP)) & 3;
                    if (ln < 4) st_pkt4(win + 0x44000 + xch_copy(1 + (ln & 1)) + (ln >> 1) * 4096 + blockIdx.x * 4, now | sq);
                    __syncwarp();
                }
                if (warp == 6 && s < NSEG - 1) {
                    asm volatile("fence.proxy.async.shared::cta;" ::: "memory");
                    expect_e(sb + MB_XA, 8192);
                    tma3d_e(sb + OFF_MEMT, &tmXB, (s + 1) * 32, 0, sb + MB_XA);
                    tma3d_e(sb + OFF_MEMT + 4096, &tmXB, (s + 1) * 32, 1, sb + MB_XA);
                }
                bar_sync(BAR_O2, 256);
            }
            if (s == NSEG - 1) break;
            const uint32_t ln = laneid();
            auto softmax = [&](auto&& more) {
                const uint32_t pb = warp * 32 + (ln & 3) * 8, kt = min(ln >> 2, 4u);
                const uint32_t pw = keep(sb + OFF_PM + pb + selu(ln < 4, 0, pb + 256 + (~kt & 1) * 8 + ((kt + 1) & 4)));
                const uint32_t sr = keep(sb + OFF_SM + kt * 256 + (pb ^ (kt & 3) * 32));
                mbar_wait(sb + MB_S, s & 1);
                const float2 u = lds2f(sr), t = lds2f(sr + (OFF_SP - OFF_SM)), w = lds2f(sr + (OFF_SP + 1280 - OFF_SM));
                more();
                float x = u.x + t.x + w.x, y = u.y + t.y + w.y;
                const int m = __float_as_int(fmaxf(x, y)), hi = __reduce_max_sync(0xffffffffu, m), lw = __reduce_min_sync(0xffffffffu, m);
                const float mx = __int_as_float(hi >= 0 ? hi : lw) * -SCL_B;
                x = ex2(fmaf(x, SCL_B, mx)); y = ex2(fmaf(y, SCL_B, mx));
                sts1(pw, pack2(x, y));
                bar_sync(BAR_PM, 384);
            };
            if (act) {
                const uint32_t wo0 = keep(sb + OFF_WO + warp * 4096 + ((ln & 7) + ((ln >> 4) << 3)) * 64 + ((((ln >> 3) & 1) ^ ((ln >> 1) & 3)) << 4)), wo1 = keep(wo0 ^ 32);
                const uint32_t tag = (__shfl_sync(0xffffffffu, lds1(sb + OFF_EP), 0) ^ s) & 1;
                uint32_t f[24][4];
                auto ld = [&](int n) { ldsm4t((out_ord(n) & 1 ? wo1 : wo0) + (out_ord(n) >> 3) * 28672 + (out_ord(n) >> 1 & 3) * 1024, f[n][0], f[n][1], f[n][2], f[n][3]); };
#pragma unroll
                for (int n = 0; n < NPE; n++) ld(n);
                softmax([&]() {
#pragma unroll
                    for (int n = NPE; n < NPM; n++) ld(n);
                });
                if (s == 0) {
                    mbar_wait_long(sb + MB_WO, 0);
#pragma unroll
                    for (int n = 0; n < NPM; n++) ld(n);
                }
#pragma unroll
                for (int n = NPM; n < NPF; n++) ld(n);
                const uint32_t l8 = keep(sb + ln * 8);
                const char* dst = nullptr;
                blk(warp);
                bar_sync(BAR_O, 384);
                float2 bb[12];
                auto ldo = [&](int i) { bb[i] = lds2f(l8 + OFF_R1 + (i + 8) % 12 * 256); };
                float e[2][4] = {{0, 0, 0, 0}, {0, 0, 0, 0}};
                int nl = NPF, nb = 0;
#pragma unroll
                for (int n = 0; n < 24; n++) {
                    const int k = out_ord(n) >> 1, t = out_ord(n) & 1;
                    if (n == 8) { bar_sync(BAR_O2, 256); }
                    if (n == 0 || n == 8) { for (int i = 0; i < (n ? NO2 : NOB); i++) ldo(nb++); blk(warp); }
                    mma16(e[t], f[n][0], f[n][1], f[n][2], f[n][3], __float_as_uint(bb[k].x), __float_as_uint(bb[k].y));
                    if ((t || (OE && n >= 8)) && nb < (n < 8 ? 4 : 12)) ldo(nb++);
                    if (n > 1 && nl < 24 && !(n < 8 && n >= 8 - (NO2 - NOB + 1) / 2) && !(OE && n >= 8 && n < 8 + OE)) ld(nl++);
                    if (n == DN) { const uint32_t o = keep(l8); dst = keepp(win + (gp + ((o & 128) << 5) + (o & 127))); }
                    if (n == 23 || (LEAD && n == 24 - LEAD)) {
                        if (n < 23 || LEAD < 2) st_pkt8(dst, (pack2(e[0][0], e[0][1]) & ~1u) | tag, pack2(e[0][2], e[0][3]));
                        if (n == 23) st_pkt8(dst + 0x2000, (pack2(e[1][0], e[1][1]) & ~1u) | tag, pack2(e[1][2], e[1][3]));
                    }
                    if (t || out_ord(n + 1) % 2 == 0) blk(warp);
                }
            } else {
                softmax([]() { });
                if (warp != 7) { bar_arrive(BAR_O, 384); bar_arrive(BAR_O2, 256); }
                else {
                    const uint32_t now = (gtime() & ~31u) | ((s - lds1(sb + OFF_EP)) & 3);
                    const char* sp = win + (lds1(sb + OFF_SPO) + min(ln, 23u) * 16);
                    expect_e(sb + MB_XB, 4096);
                    bar_sync(BAR_O, 384);
                    asm volatile("fence.proxy.async.shared::cta;" ::: "memory");
                    uint4 sv = ld_pkt(sp);
                    tma3d_e(sb + OFF_MEMT + 8192, &tmXB, (s + 1) * 32, 2, sb + MB_XB);
                    mbar_wait(sb + MB_O, s & 1);
                    bar_arrive(BAR_O2, 256);
                    blk(s);
                    int d;
                    for (int c = 0; ; c++) {
                        const int d0 = sv.x - now, d1 = sv.y - now, d2 = sv.z - now, d3 = sv.w - now;
                        d = max(max(d0, d1), max(d2, d3));
                        if (!__any_sync(0xffffffffu, (d0 | d1 | d2 | d3) & 2) || c == 512) break;
                        sv = ld_pkt(sp);
                    }
                    sts1(sb + OFF_T, (now + min(__reduce_max_sync(0xffffffffu, d), 8192)) & ~31u);
                    bar_arrive(BAR_G, 64);
                    mbar_wait(sb + MB_XA, (s + 1) & 1);
                }
            }
        }
        asm volatile("setmaxnreg.dec.sync.aligned.u32 168;");
        uint32_t f[24][4];
        const uint32_t lnt = laneid(), ep = lds1(sb + OFF_EP);
        {
            const uint32_t wo0 = sb + OFF_WO + warp * 4096 + ((lnt & 7) + ((lnt >> 4) << 3)) * 64 + ((((lnt >> 3) & 1) ^ ((lnt >> 1) & 3)) << 4);
#pragma unroll
            for (int n = 0; n < 24; n++) ldsm4t((wo0 ^ (n / 12) * 32) + (n % 12 >> 2) * 28672 + (n & 3) * 1024, f[n][0], f[n][1], f[n][2], f[n][3]);
        }
        char* tp = reinterpret_cast<char*>(g_tail) + head * 40960 + box * 2048 + lnt * 16;
#pragma unroll 1
        for (int t = 0; t < 2; t++) {
            const uint32_t b0 = (((sb + (t ? OFF_OXL : OFF_OX)) & 0x3FFFF) >> 4) | (1u << 16), b1 = (((sb + OFF_OXG + t * 8192) & 0x3FFFF) >> 4) | (1u << 16);
            float acc[2][16];
#pragma unroll
            for (int i = 0; i < 16; i++) acc[0][i] = acc[1][i] = 0.f;
            auto st = [&](int i) {
                const float* a = acc[i];
                st_pkt(tp + i * 1024, make_uint4((pack2(a[0], a[1]) & ~1u) | (ep & 1), pack2(a[2], a[3]), pack2(a[4], a[5]), pack2(a[6], a[7])));
                st_pkt(tp + i * 1024 + 512, make_uint4((pack2(a[8], a[9]) & ~1u) | (ep & 1), pack2(a[10], a[11]), pack2(a[12], a[13]), pack2(a[14], a[15])));
            };
            if (t) bar_sync(BAR_WO, 384);
            wg_fence();
            static_for<0, 8>([&](auto N) {
                constexpr int i = N.value >> 2, k = N.value & 3;
                wgmma_rs32<k * 2, k != 0>(acc[i], f[12 * i + k][0], f[12 * i + k][1], f[12 * i + k][2], f[12 * i + k][3], b0);
            });
            wg_commit();
            mbar_wait(sb + MB_F + 8 * t, 0);
            if (t) asm volatile("barrier.cluster.arrive.relaxed.aligned;" ::: "memory");
            static_for<0, 2>([&](auto I) {
                constexpr int i = I.value;
                wg_fence();
                static_for<4, 12>([&](auto K) {
                    constexpr int k = K.value;
                    wgmma_rs32<(k / 4 - 1) * 256 + (k & 3) * 2, 1>(acc[i], f[12 * i + k][0], f[12 * i + k][1], f[12 * i + k][2], f[12 * i + k][3], b1);
                });
                wg_commit();
            });
            wg_wait<1>();
            if (act) st(0);
            wg_wait<0>();
            if (act) st(1);
            if (t) bar_arrive(BAR_X, 384);
            tp += 32 * 40960;
        }
    } else {
        asm volatile("setmaxnreg.dec.sync.aligned.u32 56;");
        const int g = __reduce_max_sync(0xffffffffu, (unsigned)tid >> 5 & 3);
        if (g >= 2) pick_role(sb, false, g & 1, pp, ep0 + 1);
        const uint32_t ep = __reduce_max_sync(0xffffffffu, ep0) + 1;
        sts1(sb + OFF_EP, ep);
#pragma unroll
        for (int i = 0; i < 5; i++) {
            const unsigned short* m = reinterpret_cast<const unsigned short*>(mem0) + g * 160 + (tid & 31) + 32 * i;
            sts4(sb + (tid & 127) * 16 + (i < 4 ? OFF_SX + i * 2048 : OFF_WO + 81920),
                 make_uint4(m[0] | ((uint32_t)m[DM] << 16), m[2 * DM] | ((uint32_t)m[3 * DM] << 16),
                            m[4 * DM] | ((uint32_t)m[5 * DM] << 16), m[6 * DM] | ((uint32_t)m[7 * DM] << 16)));
        }
        asm volatile("barrier.cluster.wait.acquire.aligned;" ::: "memory");
        if (g == 0) {
            const int e0 = head * DH + rank * 64;
            for (int i = PWIN; i < 5; i++) {
                mbar_wait(sb + MB_F + 8 * (i - PWIN), 0);
                expect_e(sb + MB_F + 8 * i, 32768);
                tma2d_e(sb + OFF_WV + i * 16384, &tmWq, e0, i * 128, sb + MB_F + 8 * i);
                tma2d_e(sb + OFF_WO + i * 16384, &tmWk, e0, i * 128, sb + MB_F + 8 * i);
            }
            for (int i = 0; i < 5; i++) {
                mbar_wait(sb + MB_E + 8 * i, 0);
                if (i + 5 - PWIN < 5) mbar_wait(sb + MB_F + 8 * (i + 5 - PWIN), 0);
                expect_e(sb + MB_F + 8 * i, 16384);
                tma2d_e(sb + OFF_WV + i * 16384, &tmWv, e0, i * 128, sb + MB_F + 8 * i);
            }
        }
        uint32_t role = 0, ph = 0, tg = 0;
        uint32_t o16 = __shfl_sync(0xffffffffu, (tid & 31) * 16, tid & 31);
        auto gather = [&](int s) {
            const char* mb = win + (role >> 8 & 1) * 4096 + xch_copy((role >> 1) % NCP);
            mbar_wait(sb + MB_EM, s & 1);
            ggate(tg + G2);
            pause<F2>();
#pragma unroll
            for (int i = 0; i < 4; i++) { const int c = (i & 1) * 2 + (i >> 1); bulk_ld_e(sb + OFF_MEMT + c * 2560, mb + xch_mem(c), 2560, sb + MB_M + 8 * c); }
            bar_arrive(BAR_G, 64);
        };

        for (int s = 0; ; s++) {
            uint32_t vx[8];
            o16 += opq0<8>(s);
            const uint32_t lz = sb + o16;
            const uint4* vp = keepp(g_vx + (blockIdx.x * 64 + s) * 256 + g * 32 + (o16 >> 4));
            auto load_v = [&]() {
                const uint4 u = ld_pkt(vp), v = ld_pkt(vp + 128);
                vx[0] = u.x; vx[2] = u.y; vx[1] = u.z; vx[3] = u.w; vx[4] = v.x; vx[6] = v.y; vx[5] = v.z; vx[7] = v.w;
            };
            const char* mb = win + (role >> 8 & 1) * 4096 + xch_copy((role >> 1) % NCP);
            auto store_x = [&]() {
                if (g == 3) {
                    bar_sync(BAR_G, 64);
                    if (o16 == 0 && s < NSEG - 1) { tma_st(&tmOx, sb + OFF_OX, blockIdx.x * 64, (s - 1) * 32); asm volatile("cp.async.bulk.commit_group;" ::: "memory"); }
                    __syncwarp();
                }
            };
#pragma unroll
            for (int j = 0; j < 8; j++) vx[j] = 0;
            if (s > NVC) load_v();
            if (s >= NVC) store_x();
            if (s < NVC) {
                const uint32_t wv_lo = (((sb + OFF_WV) & 0x3FFFF) >> 4) | (64u << 16), xr_lo = (((sb + OFF_XR) & 0x3FFFF) >> 4) | (1u << 16);
                float acc[16];
#pragma unroll
                for (int i = 0; i < 16; i++) acc[i] = 0.f;
                mbar_wait(sb + MB_XA, s & 1);
                mbar_wait(sb + MB_XB, s & 1);
                static_for<0, 10>([&](auto KB) {
                    constexpr uint32_t kb = KB.value;
                    if (kb == 4) {
                        wg_wait<1>();
                        bar_sync(BAR_P, 128);
                        if (s > 0) { if (g == 1) gather(s); store_x(); }
                        else {
                            const uint32_t ln = laneid();
                            mbar_wait_long(sb + MB_EM, 0);
#pragma unroll
                            for (int i = 0; i < 5; i++)
                                sts4(sb + mem_row(ln) + OFF_MEMT + g * 2560 + 512 * i, lds4(sb + g * 512 + ln * 16 + (i < 4 ? OFF_SX + i * 2048 : OFF_WO + 81920)));
                            asm volatile("fence.proxy.async.shared::cta;" ::: "memory");
                            bar_sync(BAR_P, 128);
                            arrive_e(sb + MB_M + 8 * g);
                        }
                    }
                    if (!(kb & 1) && s == 0) {
                        mbar_wait_long(sb + MB_E + 4 * kb, 0);
                        mbar_wait_long(sb + MB_F + 4 * kb, 1);
#pragma unroll
                        for (int p = 0; p < 3; p++)
                            if (kb == (WOK >> 4 * p & 15) && g == 0) tma3d_e(sb + OFF_WO + p * 28672, &tmWo, head * DH + (rank + p) % 3 * 64, rank * 7, sb + MB_WO);
                    }
                    wg_fence();
                    static_for<0, 4>([&](auto K4) { wgmma_ss32<(kb * 4 + K4.value) * 128, xblk(kb) / 16 + K4.value * 2, (kb | K4.value) != 0>(acc, wv_lo, xr_lo); });
                    wg_commit();
                });
                wg_wait<0>();
#pragma unroll
                for (int j = 0; j < 8; j++) vx[j] = pack2(acc[2 * j], acc[2 * j + 1]);
                bar_sync(BAR_P, 128);
            }
            const uint32_t* fv = g_flagv + blockIdx.x * 64 + (s == NVC ? s : s + 1);
            uint32_t fl = ep;
            if (s == NVC || (g == 0 && s > NVC && (VFLAGS >> 1 >> s & 1))) fl = ld_relaxed(fv);
            {
                const uint32_t mt = keep(sb + OFF_MEMT + g * 2560 + o16 * 2 + (o16 >> 4 & 28)), tag = (s ^ ep ^ 1) & 1, msk = keep(s > 0);
                const int bar = keep(BAR_MEM + g);
                auto stale = [&](uint32_t m) {
                    const uint32_t w0 = lds1(mt), w1 = lds1(mt + 1024), w2 = lds1(mt + 1536);
                    return arrive_unless(tagx(w0, w1, tag) | (w2 ^ tag), m, bar, 160);
                };
                mbar_wait_long(sb + MB_M + 8 * g, s & 1);
                if (stale(msk)) {
                    for (int cnt = 0; ; cnt++) {
                        asm volatile("fence.proxy.async.shared::cta;" ::: "memory");
                        __syncwarp();
                        expect_e(sb + MB_M2 + 8 * g, 2560);
                        bulk_ld_e(sb + OFF_MEMT + g * 2560, mb + xch_mem(g), 2560, sb + MB_M2 + 8 * g);
                        mbar_wait_long(sb + MB_M2 + 8 * g, ph);
                        ph ^= 1;
                        if (!stale(cnt < WAIT_LIM)) break;
                    }
                }
            }
            if (g == 3) { asm volatile("cp.async.bulk.wait_group.read 0;" ::: "memory"); __syncwarp(); bar_arrive(BAR_R1, 288); if (RB) bar_arrive(BAR_PM, 160); }
            if (g == XG && s < NSEG - 1) {
                mbar_wait(sb + MB_EA, s & 1);
                expect_e(sb + MB_XA, NX * 4096);
                tma3d_e(sb + OFF_XR, &tmXA, (s + 1) * 32, 3, sb + MB_XA);
            }
            if (fl != ep) for (int c = 0; c < SPIN_LIM && ld_acquire(fv) != ep; c++) { }
            if (s == NVC) load_v();
            if (PFV && g == 0 && s >= NVC && s < NSEG - 1) asm volatile("prefetch.global.L2 [%0];" :: "l"(g_vx + (blockIdx.x * 64 + s + 1) * 256 + (o16 >> 1)));
            if (s < NSEG - 1) {
                if (g == 0) expect_e(sb + MB_O, 2048);
            } else if (g == 0) {
                expect_e(sb + MB_F, 8192); expect_e(sb + MB_F + 8, 8192);
            }
            if (g == 1) expect_e(sb + MB_SX, 5120);
            auto progress = [&]() {
                if (g == 3 && (PROG >> s & 1)) {
                    if (o16 == 0) {
                        asm volatile("cp.async.bulk.wait_group 0;" ::: "memory");
                        st_pkt4(g_prog + blockIdx.x + (keep(s) >> 8), ep * 128 + s);
                    }
                    __syncwarp();
                }
            };
            progress();
            const uint32_t q1 = keep(mapa(sb, (rank + 1) % 3) - sb), q2 = keep(mapa(sb, (rank + 2) % 3) - sb);
            uint32_t own[5], vm0, vm1;
            {
                const uint32_t qa_lo = (((sb + OFF_QA + 1024) & 0x3FFFF) >> 4) | (1u << 16), ka_lo = (((sb + OFF_KA) & 0x3FFFF) >> 4) | (1u << 16);
                const uint32_t va = keep(sb + ((o16 >> 1) ^ g * 32) + g * 256 + (s == NSEG - 1 ? OFF_R1L : OFF_R1) + 2048);
                float d[20];
#pragma unroll
                for (int j = 0; j < 20; j++) d[j] = 0.f;
                bar_sync(BAR_S, 288);
                const float2 u = lds2f(va), v = lds2f(va + 1024);
                role = __shfl_sync(0xffffffffu, lds1(sb + OFF_ROLE), 0);
                asm volatile("fence.proxy.async.shared::cta;" ::: "memory");
                wg_fence();
                static_for<0, 4>([&](auto K4) { wgmma_ss40<K4.value * 2, K4.value != 0>(d, qa_lo, ka_lo); });
                wg_commit();
                if (s < NSEG - 1) expect_e(sb + MB_M + 8 * g, 2560);
                vm0 = badd2(__float_as_uint(u.x), __float_as_uint(v.x)); vm1 = badd2(__float_as_uint(u.y), __float_as_uint(v.y));
                const uint32_t xo = lz + OFF_SX + g * 640, mo = sb + OFF_SX + g * 640 + 512 + (o16 >> 2);
                const int lim = 8 + 8 * g + (o16 >> 6) - ((o16 >> 3) & 6);
                wg_wait<0>();
#pragma unroll
                for (int j = 0; j < 5; j++) own[j] = pack2(8 * j > lim ? -INFINITY : d[4 * j], 8 * j + 1 > lim ? -INFINITY : d[4 * j + 1]);
                mbar_wait(sb + MB_S, s & 1);
                st_async4(q1 + xo + 2560, own[0], own[1], own[2], own[3], q1 + sb + MB_SX); st_async4(q2 + xo, own[0], own[1], own[2], own[3], q2 + sb + MB_SX);
                st_async1(q1 + mo + 2560, own[4], q1 + sb + MB_SX);                         st_async1(q2 + mo, own[4], q2 + sb + MB_SX);
            }
            if (s < NSEG - 1) {
                const uint32_t pm = keep(sb + OFF_PM + (o16 >> 1)), oo = keep(pm + (OFF_R1 - OFF_PM) + g * 256);
                blk(s);
                bar_sync(BAR_PM, 384);
                const uint4 qq = lds4(lz + OFF_PM + 256);
                const uint32_t p0 = lds1(pm);
                float oa[2][4] = {{0, 0, 0, 0}, {0, 0, 0, 0}}, ob[2][4] = {{0, 0, 0, 0}, {0, 0, 0, 0}}, os[4] = {0, 0, 0, 0};
                mma16(os, qq.x, qq.y, qq.z, qq.w, 0x3f803f80, 0x3f803f80);
                mma16(oa[0], qq.x, qq.y, qq.z, qq.w, vx[0], vx[2]);
                mma16(oa[1], qq.x, qq.y, qq.z, qq.w, vx[1], vx[3]);
                mma16(ob[0], qq.x, qq.y, qq.z, qq.w, vx[4], vx[6]);
                mma8(os, p0, 0, 0x3f803f80);
                mma16(ob[1], qq.x, qq.y, qq.z, qq.w, vx[5], vx[7]);
                mma8(oa[0], p0, 0, vm0);
                mma8(oa[1], p0, 0, vm1);
                const float inv = rcpf(os[0] + os[2]);
                const uint32_t o0 = pack2((oa[0][0] + ob[0][2]) * inv, (oa[0][1] + ob[0][3]) * inv), o1 = pack2((oa[1][0] + ob[1][2]) * inv, (oa[1][1] + ob[1][3]) * inv);
                st_async2(q1 + oo + 1024, o0, o1, q1 + sb + MB_O);
                st_async2(q2 + oo, o0, o1, q2 + sb + MB_O);
                sts2(oo + 2048, o0, o1);
                bar_arrive(BAR_O, 384);
            } else if (g == 1) {
                share_o(sb, rank, OFF_OX, 0);
            }
            {
                float sc[10], mx;
                const uint32_t xo = lz + OFF_SX + g * 640, pa = sb + OFF_SX + g * 640 + (o16 >> 2);
                mbar_wait(sb + MB_SX, s & 1);
                const uint4 u = lds4(xo), v = lds4(xo + 2560);
                const uint32_t um = lds1(pa + 512), vm = lds1(pa + 512 + 2560);
#define SSUM(k, a, b, c) sc[k] = (bf_lo(a) + bf_lo(b)) + bf_lo(c); sc[k + 1] = (bf_hi(a) + bf_hi(b)) + bf_hi(c);
                SSUM(0, own[0], u.x, v.x) SSUM(2, own[1], u.y, v.y) SSUM(4, own[2], u.z, v.z) SSUM(6, own[3], u.w, v.w) SSUM(8, own[4], um, vm)
#undef SSUM
                mx = fmaxf(fmaxf(fmaxf(sc[2], sc[3]), fmaxf(sc[4], sc[5])), fmaxf(fmaxf(fmaxf(sc[6], sc[7]), fmaxf(sc[8], sc[9])), fmaxf(sc[0], sc[1])));
                mx = fmaxf(fmaxf(mx, __shfl_xor_sync(0xffffffffu, mx, 1)), fmaxf(__shfl_xor_sync(0xffffffffu, mx, 2), __shfl_xor_sync(0xffffffffu, mx, 3)));
                mx *= -SCL_B;
                float sum = 0.f;
#pragma unroll
                for (int j = 0; j < 10; j++) { sc[j] = ex2(fmaf(sc[j], SCL_B, mx)); sum += sc[j]; }
                sum = (sum + __shfl_xor_sync(0xffffffffu, sum, 1)) + (__shfl_xor_sync(0xffffffffu, sum, 2) + __shfl_xor_sync(0xffffffffu, sum, 3));
                const float inv = rcpf(sum);
#pragma unroll
                for (int j = 0; j < 5; j++) sts1(pa + j * 128, pack2(sc[2 * j] * inv, sc[2 * j + 1] * inv));
                asm volatile("fence.proxy.async.shared::cta;" ::: "memory");
            }
            float acc[16];
            {
                const uint32_t px_lo = (((sb + OFF_SX) & 0x3FFFF) >> 4) | (8u << 16);
                uint32_t a[12];
                const uint32_t z = opq0<8>(s);
#pragma unroll
                for (int i = 0; i < 12; i++) asm volatile("xor.b32 %0, %1, %2;" : "=r"(a[i]) : "r"(i < 8 ? vx[i & 7] : i == 8 ? vm0 : i == 9 ? vm1 : 0u), "r"(z));
#pragma unroll
                for (int i = 0; i < 16; i++) acc[i] = 0.f;
                if (g == 1 && s < NSEG - 1) { bar_sync(BAR_G, 64); tg = lds1(sb + OFF_T); }
                if (s < NSEG - 1) bar_sync(BAR_WO, 384); else bar_sync(BAR_P, 128);
                wg_fence();
                wgmma_rs32n<0, 0>(acc, a[8], a[9], a[10], a[11], px_lo);
                wgmma_rs32n<8, 1>(acc, a[0], a[1], a[2], a[3], px_lo);
                wgmma_rs32n<24, 1>(acc, a[4], a[5], a[6], a[7], px_lo);
                wg_commit();
            }
            o16 += opq0<9>(s);
            const uint32_t ln = o16 >> 4;
            const uint32_t sa = keep(sb + (s == NSEG - 1 ? OFF_OXL : OFF_OX) + ((ln & 7) + ((ln >> 4) << 3)) * 128 + (((2 * g + ((ln >> 3) & 1)) ^ (ln & 7)) << 4));
            auto store_o = [&]() {
                wg_wait<0>();
                stsm4t(sa, pack2v(acc[0], acc[1]), pack2v(acc[2], acc[3]), pack2v(acc[4], acc[5]), pack2v(acc[6], acc[7]));
                stsm4t(sa + 2048, pack2v(acc[8], acc[9]), pack2v(acc[10], acc[11]), pack2v(acc[12], acc[13]), pack2v(acc[14], acc[15]));
            };
            if ((role & 255) < 80 && s < NSEG - 1) {
                const char* rp = keepp(win + (XCH_PART + (role & 255) * 4096 + g * 1024 + (o16 >> 1)));
                const char* wp = keepp(win + ((role >> 9 << 7) + (((o16 >> 4 ^ role) & 1) * 4 + (o16 >> 7)) * 16 + (o16 >> 3 & 12)));
                const uint32_t tag = (s ^ ep) & 1, rb = keep(sb + (o16 >> 1));
                uint32_t x[4], y[4];
                auto load = [&]() { static_for<0, 4>([&](auto I) { ld_pkt8<I.value * 256>(x[I.value], y[I.value], rp); }); };
                auto sum8 = [&](uint32_t m) {
                    sts4(sb + o16 + OFF_RED + g * 512,
                         make_uint4(__float_as_uint(((bf_lo(x[0]) + bf_lo(x[1])) + bf_lo(x[2])) + bf_lo(x[3])), __float_as_uint(((bf_hi(x[0]) + bf_hi(x[1])) + bf_hi(x[2])) + bf_hi(x[3])),
                                    __float_as_uint(((bf_lo(y[0]) + bf_lo(y[1])) + bf_lo(y[2])) + bf_lo(y[3])), __float_as_uint(((bf_hi(y[0]) + bf_hi(y[1])) + bf_hi(y[2])) + bf_hi(y[3]))));
                    return sync_unless(tagx(x[0], x[1], tag), tagx(x[2], x[3], tag), m, BAR_R, 128);
                };
                auto again = [&]() { for (int cnt = 0; ; cnt++) { load(); if (!sum8(cnt < WAIT_LIM)) break; } };
                if (g == 0) {
                    bar_sync(BAR_R, 128);
                    load();
                    store_o();
                    const bool st = sum8(1);
                    float2 r[8];
#pragma unroll
                    for (int i = 0; i < 8; i++) r[i] = lds2f(rb + OFF_RED + i * 256);
                    if (REL == 1 && s >= NVC - 1) bar_arrive(BAR_PUB, 288);
                    if (st) {
                        again();
#pragma unroll
                        for (int i = 0; i < 8; i++) r[i] = lds2f(rb + OFF_RED + i * 256);
                    }
                    const float k0 = ((r[0].x + r[1].x) + (r[2].x + r[3].x)) + ((r[4].x + r[5].x) + (r[6].x + r[7].x));
                    const float k1 = ((r[0].y + r[1].y) + (r[2].y + r[3].y)) + ((r[4].y + r[5].y) + (r[6].y + r[7].y));
                    const uint32_t kb = __float_as_uint(k0);
                    const uint32_t pk = __byte_perm(kb + ((kb ^ tag << 16) & 0x10000), pack2(0.f, k1), 0x7632);
#pragma unroll
                    for (int i = 0; i < 2 * NCP; i++) st_pkt4(wp + xch_copy(i >> 1) + (i & 1) * 4096, pk);
                    if (REL == 2 && s >= NVC - 1) bar_arrive(BAR_PUB, 288);
                } else {
                    if (g == 1) { ggate(tg + G1); pause<F1>(); }
                    bar_sync(BAR_R, 128);
                    load();
                    store_o();
                    if (sum8(1)) again();
                }
            } else {
                store_o();
                if (s == NSEG - 1) {
                    asm volatile("fence.proxy.async.shared::cta;" ::: "memory");
                    bar_arrive(BAR_WO, 384);
                    bar_sync(BAR_P, 128);
                    if (g == 1) share_o(sb, rank, OFF_OXL, 1);
                    break;
                }
                bar_sync(BAR_R, 128);
                if (g == 0 && s >= NVC - 1) bar_arrive(BAR_PUB, 288);
            }
            if (g == 1 && s >= NVC - 1) gather(s + 1);
            if (g == 3) asm volatile("fence.proxy.async.shared::cta;" ::: "memory");
        }
        uint32_t u, c, sb2;
        asm volatile("mov.u32 %0, %%tid.x; mov.u32 %1, %%ctaid.x; mov.u32 %2, %%dynamic_smem_size;" : "=r"(u), "=r"(c), "=r"(sb2));
        sb2 += sb - CHAIN_SMEM;
        const uint32_t g2 = __shfl_sync(0xffffffffu, (u >> 5) & 3, 0), ln = u & 31;
        asm volatile("barrier.cluster.arrive.relaxed.aligned;" ::: "memory");
        asm volatile("setmaxnreg.inc.sync.aligned.u32 96;");
        const uint32_t et = lds1(sb2 + OFF_EP);
        const uint4* rp = g_tail + g2 * 8 * 2560 + c * 32 + ln;
        bf16* op = out + (size_t)((NSEG - 2) * 32 + (c & 1) * 16 + (g2 >> 1) * 8 + (ln >> 2)) * OUTW + DM + (c >> 1) * 16 + (g2 & 1) * 8 + (ln & 3) * 2;
#pragma unroll 1
        for (int t = 0; t < 2; t++) {
            if (t) bar_sync(BAR_X, 384);
            if (c >= 80) continue;
            spin(t ? TXE : TXD);
            uint4 q[8];
#pragma unroll
            for (int i = 0; i < 8; i++) q[i] = ld_pkt(rp + 2560 * i);
            for (int cnt = 4 * WAIT_LIM; cnt; cnt--) {
                uint32_t bad = 0;
#pragma unroll
                for (int i = 0; i < 8; i++) bad |= q[i].x ^ et;
                if (!any_bit0(bad, bad)) break;
                static_for<0, 8>([&](auto I) { ld_pkt_stale<I.value * 40960>(q[I.value], rp, et); });
            }
            float r[8] = {0, 0, 0, 0, 0, 0, 0, 0};
#pragma unroll
            for (int i = 0; i < 8; i++) {
                r[0] += bf_lo(q[i].x); r[1] += bf_hi(q[i].x); r[2] += bf_lo(q[i].y); r[3] += bf_hi(q[i].y);
                r[4] += bf_lo(q[i].z); r[5] += bf_hi(q[i].z); r[6] += bf_lo(q[i].w); r[7] += bf_hi(q[i].w);
            }
            const uint32_t ra = sb2 + OFF_TRED + t * 4096 + ln * 8, rb2 = ra + g2 * 1024;
#pragma unroll
            for (int j = 0; j < 4; j++) sts2(ra + j * 1024 + g2 * 256, __float_as_uint(r[2 * j]), __float_as_uint(r[2 * j + 1]));
            bar_sync(BAR_R, 128);
            const float2 x0 = lds2f(rb2), x1 = lds2f(rb2 + 256), x2 = lds2f(rb2 + 512), x3 = lds2f(rb2 + 768);
            stg1(op, movm(pack2((x0.x + x1.x) + (x2.x + x3.x), (x0.y + x1.y) + (x2.y + x3.y))));
            rp += 32 * 2560;
            op += 32 * OUTW;
        }
    }
    asm volatile("barrier.cluster.wait.aligned;" ::: "memory");
}

constexpr int NSIDE = 36, SST = 3, MAXJ = 44, NKS = 7;
constexpr uint32_t S_STAGE = 49152, S_STG = SST * S_STAGE, S_RST = S_STG + 65536, S_BAR = S_RST + 12288, SIDE_SMEM = S_BAR + 256;
constexpr uint32_t SB_FULL = S_BAR, SB_EMPTY = S_BAR + 64, SB_STAGED = S_BAR + 32, SB_FREE = S_BAR + 48;
constexpr uint32_t SB_FINE = 128;
enum { JV = 0, JQ = 1, JP = 2, JO = 3, JR = 4, JEND = 5 };
struct SideParams {
    bf16* out;
    CUtensorMap a[4], b[4], c[4], st[2], sto;
};
struct Job { uint32_t x, y; };
struct JobTable { Job j[NSIDE][MAXJ]; };
static_assert(OFF_OX % 1024 == 0 && OFF_QA % 1024 == 0 && OFF_MEMT % 1024 == 0, "swizzled tiles");
__constant__ const JobTable c_jobs = {{
    {{0x4020,0xa0000},{0x5220,0xa0000},{0xcc20,0xa0000},{0x641,0xa0000},{0x10341,0xa0000},{0x20640,0xa0000},{0x43,0x600000},{0x51540,0xa0000},{0x602c0,0xa0000},{0x60d40,0xa0000},{0x617c0,0xa0000},{0x40043,0x10e0400},{0x70340,0xa0000},{0x71040,0xa0000},{0x50043,0x10e0500},{0x60023,0x10e0600},{0x2360223,0x10d0605},{0x70023,0x10e0800},{0x78013,0x10e0900},{0x70024,0x1000800},{0x70224,0x1000802},{0x5,0x0},{0x40044,0x1000400},{0x50044,0x1000500},{0x60024,0x1000600},{0x68024,0x1000700}},
    {{0x40a0,0xa0000},{0x52a0,0xa0000},{0xcca0,0xa0000},{0x6c1,0xa0000},{0x103c1,0xa0000},{0x206c0,0xa0000},{0xc3,0x600000},{0x515c0,0xa0000},{0x60340,0xa0000},{0x60dc0,0xa0000},{0x50042,0xa0000},{0x400c3,0x10e0400},{0x703c0,0xa0000},{0x710c0,0xa0000},{0x500c3,0x10e0500},{0x600a3,0x10e0600},{0x680a3,0x10e0700},{0x700a3,0x10e0800},{0x78093,0x10e0900},{0x700a4,0x1000800},{0x78094,0x1000900},{0x5,0x0},{0x400c4,0x1000400},{0x500c4,0x1000500},{0x600a4,0x1000600},{0x680a4,0x1000700}},
    {{0x4120,0xa0000},{0x5320,0xa0000},{0xcd20,0xa0000},{0x741,0xa0000},{0x10441,0xa0000},{0x20740,0xa0000},{0x143,0x600000},{0x51640,0xa0000},{0x603c0,0xa0000},{0x60e40,0xa0000},{0x500c2,0xa0000},{0x40143,0x10e0400},{0x70440,0xa0000},{0x71140,0xa0000},{0x50143,0x10e0500},{0x60123,0x10e0600},{0x68123,0x10e0700},{0x70123,0x10e0800},{0x78113,0x10e0900},{0x70124,0x1000800},{0x78114,0x1000900},{0x5,0x0},{0x40144,0x1000400},{0x50144,0x1000500},{0x60124,0x1000600},{0x68124,0x1000700}},
    {{0x41a0,0xa0000},{0x53a0,0xa0000},{0xcda0,0xa0000},{0x14030,0xa0000},{0x150b0,0xa0000},{0x20341,0xa0000},{0x20dc0,0xa0000},{0x30541,0xa0000},{0x505c1,0xa0000},{0x30dc0,0xa0000},{0x602c1,0xa0000},{0x705c1,0xa0000},{0x408c0,0xa0000},{0x415c0,0xa0000},{0x505c0,0xa0000},{0x51040,0xa0000},{0x40042,0xa0000},{0x60840,0xa0000},{0x612c0,0xa0000},{0x401c3,0x10e0400},{0x600c2,0xa0000},{0x70b40,0xa0000},{0x501c3,0x10e0500},{0x700c2,0xa0000},{0x681a3,0x10e0700},{0x701a3,0x10e0800},{0x78193,0x10e0900},{0x701a4,0x1000800},{0x78194,0x1000900},{0x5,0x0},{0x401c4,0x1000400},{0x501c4,0x1000500},{0x601a4,0x1000600},{0x681a4,0x1000700}},
    {{0x4220,0xa0000},{0x5420,0xa0000},{0xce20,0xa0000},{0x140b0,0xa0000},{0x15130,0xa0000},{0x203c1,0xa0000},{0x20e40,0xa0000},{0x305c1,0xa0000},{0x50641,0xa0000},{0x30e40,0xa0000},{0x60341,0xa0000},{0x70641,0xa0000},{0x40940,0xa0000},{0x41640,0xa0000},{0x50640,0xa0000},{0x510c0,0xa0000},{0x400c2,0xa0000},{0x608c0,0xa0000},{0x61340,0xa0000},{0x40243,0x10e0400},{0x60142,0xa0000},{0x70bc0,0xa0000},{0x50243,0x10e0500},{0x70142,0xa0000},{0x68223,0x10e0700},{0x70223,0x10e0800},{0x78213,0x10e0900},{0x70224,0x1000800},{0x78214,0x1000900},{0x5,0x0},{0x40244,0x1000400},{0x50244,0x1000500},{0x60224,0x1000600},{0x68224,0x1000700}},
    {{0x42a0,0xa0000},{0x54a0,0xa0000},{0xcea0,0xa0000},{0x14130,0xa0000},{0x151b0,0xa0000},{0x20441,0xa0000},{0x20ec0,0xa0000},{0x30641,0xa0000},{0x506c1,0xa0000},{0x30ec0,0xa0000},{0x603c1,0xa0000},{0x706c1,0xa0000},{0x409c0,0xa0000},{0x416c0,0xa0000},{0x506c0,0xa0000},{0x51140,0xa0000},{0x40142,0xa0000},{0x60940,0xa0000},{0x613c0,0xa0000},{0x740043,0x10e0401},{0x601c2,0xa0000},{0x70c40,0xa0000},{0x750043,0x10e0501},{0x701c2,0xa0000},{0x768023,0x10e0701},{0x770023,0x10e0801},{0x778013,0x10e0901},{0x70024,0x1000801},{0x78014,0x1000901},{0x5,0x0},{0x40044,0x1000401},{0x50044,0x1000501},{0x60024,0x1000601},{0x68024,0x1000701}},
    {{0x4320,0xa0000},{0x5520,0xa0000},{0xcf20,0xa0000},{0x141b0,0xa0000},{0x15230,0xa0000},{0x204c1,0xa0000},{0x20f40,0xa0000},{0x306c1,0xa0000},{0x50741,0xa0000},{0x30f40,0xa0000},{0x60441,0xa0000},{0x70741,0xa0000},{0x40a40,0xa0000},{0x41740,0xa0000},{0x50740,0xa0000},{0x511c0,0xa0000},{0x401c2,0xa0000},{0x609c0,0xa0000},{0x61440,0xa0000},{0x7400c3,0x10e0401},{0x60242,0xa0000},{0x70cc0,0xa0000},{0x7500c3,0x10e0501},{0x70242,0xa0000},{0x7680a3,0x10e0701},{0x7700a3,0x10e0801},{0x778093,0x10e0901},{0x700a4,0x1000801},{0x78094,0x1000901},{0x5,0x0},{0x400c4,0x1000401},{0x500c4,0x1000501},{0x600a4,0x1000601},{0x680a4,0x1000701}},
    {{0x43a0,0xa0000},{0x55a0,0xa0000},{0xcfa0,0xa0000},{0x14230,0xa0000},{0x152b0,0xa0000},{0x20541,0xa0000},{0x20fc0,0xa0000},{0x30741,0xa0000},{0x30040,0xa0000},{0x30fc0,0xa0000},{0x604c1,0xa0000},{0x10042,0xa0000},{0x40ac0,0xa0000},{0x417c0,0xa0000},{0x507c0,0xa0000},{0x51240,0xa0000},{0x40242,0xa0000},{0x60a40,0xa0000},{0x614c0,0xa0000},{0x740143,0x10e0401},{0x70040,0xa0000},{0x70d40,0xa0000},{0x750143,0x10e0501},{0x760123,0x10e0601},{0x7600a3,0x10e0601},{0x768123,0x10e0701},{0x770123,0x10e0801},{0x778113,0x10e0901},{0x78114,0x1000901},{0x5,0x0},{0x40144,0x1000401},{0x50144,0x1000501},{0x60124,0x1000601},{0x68124,0x1000701}},
    {{0x4420,0xa0000},{0x5620,0xa0000},{0xd020,0xa0000},{0x142b0,0xa0000},{0x15330,0xa0000},{0x205c1,0xa0000},{0x21040,0xa0000},{0x40041,0xa0000},{0x300c0,0xa0000},{0x31040,0xa0000},{0x60541,0xa0000},{0x100c2,0xa0000},{0x40b40,0xa0000},{0x20043,0x600200},{0x71340,0xa0000},{0x7501c3,0x10e0501},{0x7601a3,0x10e0601},{0x7681a3,0x10e0701},{0x7701a3,0x10e0801},{0x778193,0x10e0901},{0x701a4,0x1000801},{0x78194,0x1000901},{0x5,0x0},{0x401c4,0x1000401},{0x501c4,0x1000501},{0x601a4,0x1000601},{0x681a4,0x1000701}},
    {{0x44a0,0xa0000},{0x56a0,0xa0000},{0xd0a0,0xa0000},{0x14330,0xa0000},{0x153b0,0xa0000},{0x20641,0xa0000},{0x210c0,0xa0000},{0x400c1,0xa0000},{0x30140,0xa0000},{0x310c0,0xa0000},{0x605c1,0xa0000},{0x10142,0xa0000},{0x40bc0,0xa0000},{0x200c3,0x600200},{0x713c0,0xa0000},{0x750243,0x10e0501},{0x760223,0x10e0601},{0x768223,0x10e0701},{0x770223,0x10e0801},{0x778213,0x10e0901},{0x70224,0x1000801},{0x78214,0x1000901},{0x5,0x0},{0x40244,0x1000401},{0x50244,0x1000501},{0x60224,0x1000601},{0x68224,0x1000701}},
    {{0x4520,0xa0000},{0x5720,0xa0000},{0xd120,0xa0000},{0x143b0,0xa0000},{0x15430,0xa0000},{0x206c1,0xa0000},{0x21140,0xa0000},{0x40141,0xa0000},{0x301c0,0xa0000},{0x31140,0xa0000},{0x60641,0xa0000},{0x101c2,0xa0000},{0x40c40,0xa0000},{0x20143,0x600200},{0x71440,0xa0000},{0xe50043,0x10e0502},{0xe60023,0x10e0602},{0xe68023,0x10e0702},{0xe70023,0x10e0802},{0xe78013,0x10e0902},{0x70024,0x1000802},{0x78014,0x1000902},{0x5,0x0},{0x40044,0x1000402},{0x50044,0x1000502},{0x60024,0x1000602},{0x68024,0x1000702}},
    {{0x45a0,0xa0000},{0x57a0,0xa0000},{0xd1a0,0xa0000},{0x14430,0xa0000},{0x154b0,0xa0000},{0x20741,0xa0000},{0x211c0,0xa0000},{0x401c1,0xa0000},{0x30240,0xa0000},{0x311c0,0xa0000},{0x606c1,0xa0000},{0x10242,0xa0000},{0x40cc0,0xa0000},{0x201c3,0x600200},{0x714c0,0xa0000},{0xe500c3,0x10e0502},{0xe600a3,0x10e0602},{0xe680a3,0x10e0702},{0xe700a3,0x10e0802},{0xe78093,0x10e0902},{0x700a4,0x1000802},{0x78094,0x1000902},{0x5,0x0},{0x400c4,0x1000402},{0x500c4,0x1000502},{0x600a4,0x1000602},{0x680a4,0x1000702}},
    {{0x4620,0xa0000},{0xc020,0xa0000},{0xd220,0xa0000},{0x144b0,0xa0000},{0x15530,0xa0000},{0x20040,0xa0000},{0x21240,0xa0000},{0x40241,0xa0000},{0x302c0,0xa0000},{0x31240,0xa0000},{0x60741,0xa0000},{0x40040,0xa0000},{0x40d40,0xa0000},{0x20243,0x600200},{0x71540,0xa0000},{0xe50143,0x10e0502},{0xe60123,0x10e0602},{0xe68123,0x10e0702},{0xe70123,0x10e0802},{0xe78113,0x10e0902},{0x70124,0x1000802},{0x78114,0x1000902},{0x5,0x0},{0x40144,0x1000402},{0x50144,0x1000502},{0x60124,0x1000602},{0x68124,0x1000702}},
    {{0x46a0,0xa0000},{0xc0a0,0xa0000},{0xd2a0,0xa0000},{0x14530,0xa0000},{0x155b0,0xa0000},{0x200c0,0xa0000},{0x212c0,0xa0000},{0x402c1,0xa0000},{0x30340,0xa0000},{0x312c0,0xa0000},{0x42,0xa0000},{0x400c0,0xa0000},{0x40dc0,0xa0000},{0x20042,0xa0000},{0x50840,0xa0000},{0x512c0,0xa0000},{0x60040,0xa0000},{0x60ac0,0xa0000},{0x61540,0xa0000},{0xe401c3,0x10e0402},{0x700c0,0xa0000},{0x70dc0,0xa0000},{0xe501c3,0x10e0502},{0xe601a3,0x10e0602},{0x601a3,0x10e0600},{0xe681a3,0x10e0702},{0xe701a3,0x10e0802},{0xe78193,0x10e0902},{0x78194,0x1000902},{0x5,0x0},{0x401c4,0x1000402},{0x501c4,0x1000502},{0x601a4,0x1000602},{0x681a4,0x1000702}},
    {{0x4720,0xa0000},{0xc120,0xa0000},{0xd320,0xa0000},{0x145b0,0xa0000},{0x15630,0xa0000},{0x20140,0xa0000},{0x21340,0xa0000},{0x40341,0xa0000},{0x303c0,0xa0000},{0x31340,0xa0000},{0xc2,0xa0000},{0x40140,0xa0000},{0x40e40,0xa0000},{0x200c2,0xa0000},{0x508c0,0xa0000},{0x51340,0xa0000},{0x600c0,0xa0000},{0x60b40,0xa0000},{0x615c0,0xa0000},{0xe40243,0x10e0402},{0x70140,0xa0000},{0x70e40,0xa0000},{0xe50243,0x10e0502},{0xe60223,0x10e0602},{0x60223,0x10e0600},{0xe68223,0x10e0702},{0xe70223,0x10e0802},{0xe78213,0x10e0902},{0x78214,0x1000902},{0x5,0x0},{0x40244,0x1000402},{0x50244,0x1000502},{0x60224,0x1000602},{0x68224,0x1000702}},
    {{0x47a0,0xa0000},{0xc1a0,0xa0000},{0xd3a0,0xa0000},{0x14630,0xa0000},{0x156b0,0xa0000},{0x201c0,0xa0000},{0x213c0,0xa0000},{0x403c1,0xa0000},{0x30440,0xa0000},{0x313c0,0xa0000},{0x142,0xa0000},{0x401c0,0xa0000},{0x40ec0,0xa0000},{0x20142,0xa0000},{0x50940,0xa0000},{0x513c0,0xa0000},{0x60140,0xa0000},{0x60bc0,0xa0000},{0x61640,0xa0000},{0x1540043,0x10e0403},{0x701c0,0xa0000},{0x70ec0,0xa0000},{0x1550043,0x10e0503},{0x1560023,0x10e0603},{0x23600a3,0x10d0605},{0x1568023,0x10e0703},{0x1570023,0x10e0803},{0x1578013,0x10e0903},{0x70024,0x1000803},{0x78014,0x1000903},{0x5,0x0},{0x40044,0x1000403},{0x50044,0x1000503},{0x60024,0x1000603},{0x68024,0x1000703}},
    {{0x4820,0xa0000},{0xc220,0xa0000},{0xd420,0xa0000},{0x146b0,0xa0000},{0x15730,0xa0000},{0x20240,0xa0000},{0x21440,0xa0000},{0x40441,0xa0000},{0x304c0,0xa0000},{0x31440,0xa0000},{0x1c2,0xa0000},{0x40240,0xa0000},{0x40f40,0xa0000},{0x201c2,0xa0000},{0x509c0,0xa0000},{0x51440,0xa0000},{0x601c0,0xa0000},{0x60c40,0xa0000},{0x616c0,0xa0000},{0x15400c3,0x10e0403},{0x70240,0xa0000},{0x70f40,0xa0000},{0x15500c3,0x10e0503},{0x15600a3,0x10e0603},{0x2360123,0x10d0605},{0x15680a3,0x10e0703},{0x15700a3,0x10e0803},{0x1578093,0x10e0903},{0x700a4,0x1000803},{0x78094,0x1000903},{0x5,0x0},{0x400c4,0x1000403},{0x500c4,0x1000503},{0x600a4,0x1000603},{0x680a4,0x1000703}},
    {{0x48a0,0xa0000},{0xc2a0,0xa0000},{0xd4a0,0xa0000},{0x14730,0xa0000},{0x157b0,0xa0000},{0x202c0,0xa0000},{0x214c0,0xa0000},{0x404c1,0xa0000},{0x30540,0xa0000},{0x314c0,0xa0000},{0x242,0xa0000},{0x402c0,0xa0000},{0x40fc0,0xa0000},{0x20242,0xa0000},{0x50a40,0xa0000},{0x514c0,0xa0000},{0x60240,0xa0000},{0x60cc0,0xa0000},{0x61740,0xa0000},{0x1540143,0x10e0403},{0x702c0,0xa0000},{0x70fc0,0xa0000},{0x1550143,0x10e0503},{0x1560123,0x10e0603},{0x23601a3,0x10d0605},{0x1568123,0x10e0703},{0x1570123,0x10e0803},{0x1578113,0x10e0903},{0x70124,0x1000803},{0x78114,0x1000903},{0x5,0x0},{0x40144,0x1000403},{0x50144,0x1000503},{0x60124,0x1000603},{0x68124,0x1000703}},
    {{0x4920,0xa0000},{0xc320,0xa0000},{0xd520,0xa0000},{0x147b0,0xa0000},{0x10041,0xa0000},{0x20340,0xa0000},{0x21540,0xa0000},{0x40541,0xa0000},{0x305c0,0xa0000},{0x31540,0xa0000},{0x70041,0xa0000},{0x40340,0xa0000},{0x41040,0xa0000},{0x50040,0xa0000},{0x50ac0,0xa0000},{0x516c0,0xa0000},{0x60440,0xa0000},{0x60ec0,0xa0000},{0x50142,0xa0000},{0x15401c3,0x10e0403},{0x704c0,0xa0000},{0x711c0,0xa0000},{0x15501c3,0x10e0503},{0x15601a3,0x10e0603},{0x15681a3,0x10e0703},{0x15701a3,0x10e0803},{0x1578193,0x10e0903},{0x701a4,0x1000803},{0x78194,0x1000903},{0x5,0x0},{0x401c4,0x1000403},{0x501c4,0x1000503},{0x601a4,0x1000603},{0x681a4,0x1000703}},
    {{0x49a0,0xa0000},{0xc3a0,0xa0000},{0xd5a0,0xa0000},{0x14830,0xa0000},{0x100c1,0xa0000},{0x203c0,0xa0000},{0x215c0,0xa0000},{0x405c1,0xa0000},{0x30640,0xa0000},{0x315c0,0xa0000},{0x700c1,0xa0000},{0x403c0,0xa0000},{0x410c0,0xa0000},{0x500c0,0xa0000},{0x50b40,0xa0000},{0x51740,0xa0000},{0x604c0,0xa0000},{0x60f40,0xa0000},{0x501c2,0xa0000},{0x1540243,0x10e0403},{0x70540,0xa0000},{0x71240,0xa0000},{0x1550243,0x10e0503},{0x1560223,0x10e0603},{0x1568223,0x10e0703},{0x1570223,0x10e0803},{0x1578213,0x10e0903},{0x70224,0x1000803},{0x78214,0x1000903},{0x5,0x0},{0x40244,0x1000403},{0x50244,0x1000503},{0x60224,0x1000603},{0x68224,0x1000703}},
    {{0x4a20,0xa0000},{0xc420,0xa0000},{0xd620,0xa0000},{0x148b0,0xa0000},{0x10141,0xa0000},{0x20440,0xa0000},{0x21640,0xa0000},{0x40641,0xa0000},{0x306c0,0xa0000},{0x31640,0xa0000},{0x70141,0xa0000},{0x40440,0xa0000},{0x41140,0xa0000},{0x50140,0xa0000},{0x50bc0,0xa0000},{0x517c0,0xa0000},{0x60540,0xa0000},{0x60fc0,0xa0000},{0x50242,0xa0000},{0x1c40043,0x10e0404},{0x705c0,0xa0000},{0x712c0,0xa0000},{0x1c50043,0x10e0504},{0x1c60023,0x10e0604},{0x1c68023,0x10e0704},{0x1c70023,0x10e0804},{0x1c78013,0x10e0904},{0x70024,0x1000804},{0x78014,0x1000904},{0x5,0x0},{0x40044,0x1000404},{0x50044,0x1000504},{0x60024,0x1000604},{0x68024,0x1000704}},
    {{0x4aa0,0xa0000},{0xc4a0,0xa0000},{0xd6a0,0xa0000},{0x14930,0xa0000},{0x101c1,0xa0000},{0x204c0,0xa0000},{0x216c0,0xa0000},{0x406c1,0xa0000},{0x30740,0xa0000},{0x316c0,0xa0000},{0x701c1,0xa0000},{0x404c0,0xa0000},{0x411c0,0xa0000},{0x501c0,0xa0000},{0x50c40,0xa0000},{0x30042,0xa0000},{0x605c0,0xa0000},{0x61040,0xa0000},{0x1c400c3,0x10e0404},{0x29c00c3,0x10d0406},{0x706c0,0xa0000},{0x71640,0xa0000},{0x1c500c3,0x10e0504},{0x1c600a3,0x10e0604},{0x1c680a3,0x10e0704},{0x1c700a3,0x10e0804},{0x1c78093,0x10e0904},{0x700a4,0x1000804},{0x78094,0x1000904},{0x5,0x0},{0x400c4,0x1000404},{0x500c4,0x1000504},{0x600a4,0x1000604},{0x680a4,0x1000704}},
    {{0x4b20,0xa0000},{0xc520,0xa0000},{0xd720,0xa0000},{0x149b0,0xa0000},{0x10241,0xa0000},{0x20540,0xa0000},{0x21740,0xa0000},{0x40741,0xa0000},{0x307c0,0xa0000},{0x31740,0xa0000},{0x70241,0xa0000},{0x40540,0xa0000},{0x41240,0xa0000},{0x50240,0xa0000},{0x50cc0,0xa0000},{0x300c2,0xa0000},{0x60640,0xa0000},{0x610c0,0xa0000},{0x1c40143,0x10e0404},{0x29c0143,0x10d0406},{0x70740,0xa0000},{0x716c0,0xa0000},{0x1c50143,0x10e0504},{0x1c60123,0x10e0604},{0x1c68123,0x10e0704},{0x1c70123,0x10e0804},{0x1c78113,0x10e0904},{0x70124,0x1000804},{0x78114,0x1000904},{0x5,0x0},{0x40144,0x1000404},{0x50144,0x1000504},{0x60124,0x1000604},{0x68124,0x1000704}},
    {{0x4ba0,0xa0000},{0xc5a0,0xa0000},{0xd7a0,0xa0000},{0x14a30,0xa0000},{0x102c1,0xa0000},{0x205c0,0xa0000},{0x217c0,0xa0000},{0x50041,0xa0000},{0x30840,0xa0000},{0x317c0,0xa0000},{0x702c1,0xa0000},{0x405c0,0xa0000},{0x412c0,0xa0000},{0x502c0,0xa0000},{0x50d40,0xa0000},{0x30142,0xa0000},{0x606c0,0xa0000},{0x61140,0xa0000},{0x1c401c3,0x10e0404},{0x29c01c3,0x10d0406},{0x707c0,0xa0000},{0x71740,0xa0000},{0x1c501c3,0x10e0504},{0x1c601a3,0x10e0604},{0x1c681a3,0x10e0704},{0x1c701a3,0x10e0804},{0x1c78193,0x10e0904},{0x701a4,0x1000804},{0x78194,0x1000904},{0x5,0x0},{0x401c4,0x1000404},{0x501c4,0x1000504},{0x601a4,0x1000604},{0x681a4,0x1000704}},
    {{0x4c20,0xa0000},{0xc620,0xa0000},{0x41,0xa0000},{0x14ab0,0xa0000},{0x104c1,0xa0000},{0x207c0,0xa0000},{0x1c3,0x600000},{0x301c2,0xa0000},{0x60740,0xa0000},{0x611c0,0xa0000},{0x1c40243,0x10e0404},{0x60042,0xa0000},{0x70640,0xa0000},{0x715c0,0xa0000},{0x1c50243,0x10e0504},{0x1c60223,0x10e0604},{0x1c68223,0x10e0704},{0x1c70223,0x10e0804},{0x1c78213,0x10e0904},{0x70224,0x1000804},{0x78214,0x1000904},{0x5,0x0},{0x40244,0x1000404},{0x50244,0x1000504},{0x60224,0x1000604},{0x68224,0x1000704}},
    {{0x4ca0,0xa0000},{0xc6a0,0xa0000},{0xc1,0xa0000},{0x14b30,0xa0000},{0x10541,0xa0000},{0x20840,0xa0000},{0x243,0x600000},{0x30242,0xa0000},{0x607c0,0xa0000},{0x61240,0xa0000},{0x2340043,0x10d0405},{0x29c0243,0x10d0406},{0x70840,0xa0000},{0x717c0,0xa0000},{0x2350043,0x10d0505},{0x2360023,0x10d0605},{0x2368023,0x10d0705},{0x2370023,0x10d0805},{0x2378013,0x10d0905},{0x70024,0x1000805},{0x78014,0x1000905},{0x5,0x0},{0x40044,0x1000405},{0x50044,0x1000505},{0x60024,0x1000605},{0x68024,0x1000705}},
    {{0x4d20,0xa0000},{0xc720,0xa0000},{0x141,0xa0000},{0x14bb0,0xa0000},{0x105c1,0xa0000},{0x208c0,0xa0000},{0x30041,0xa0000},{0x500c1,0xa0000},{0x308c0,0xa0000},{0x10043,0x600100},{0x23400c3,0x10d0405},{0xe40043,0x10e0402},{0x708c0,0xa0000},{0x23500c3,0x10d0505},{0x29d00c3,0x10d0506},{0x23680a3,0x10d0705},{0x23700a3,0x10d0805},{0x2378093,0x10d0905},{0x700a4,0x1000805},{0x78094,0x1000905},{0x5,0x0},{0x400c4,0x1000405},{0x500c4,0x1000505},{0x600a4,0x1000605},{0x680a4,0x1000705}},
    {{0x4da0,0xa0000},{0xc7a0,0xa0000},{0x1c1,0xa0000},{0x14c30,0xa0000},{0x10641,0xa0000},{0x20940,0xa0000},{0x300c1,0xa0000},{0x50141,0xa0000},{0x30940,0xa0000},{0x100c3,0x600100},{0x2340143,0x10d0405},{0xe400c3,0x10e0402},{0x70940,0xa0000},{0x2350143,0x10d0505},{0x29d0143,0x10d0506},{0x2368123,0x10d0705},{0x2370123,0x10d0805},{0x2378113,0x10d0905},{0x70124,0x1000805},{0x78114,0x1000905},{0x5,0x0},{0x40144,0x1000405},{0x50144,0x1000505},{0x60124,0x1000605},{0x68124,0x1000705}},
    {{0x4e20,0xa0000},{0xc820,0xa0000},{0x241,0xa0000},{0x14cb0,0xa0000},{0x106c1,0xa0000},{0x209c0,0xa0000},{0x30141,0xa0000},{0x501c1,0xa0000},{0x309c0,0xa0000},{0x10143,0x600100},{0x23401c3,0x10d0405},{0xe40143,0x10e0402},{0x709c0,0xa0000},{0x23501c3,0x10d0505},{0x29d01c3,0x10d0506},{0x23681a3,0x10d0705},{0x23701a3,0x10d0805},{0x2378193,0x10d0905},{0x701a4,0x1000805},{0x78194,0x1000905},{0x5,0x0},{0x401c4,0x1000405},{0x501c4,0x1000505},{0x601a4,0x1000605},{0x681a4,0x1000705}},
    {{0x4ea0,0xa0000},{0xc8a0,0xa0000},{0x2c1,0xa0000},{0x14d30,0xa0000},{0x10741,0xa0000},{0x20a40,0xa0000},{0x301c1,0xa0000},{0x50241,0xa0000},{0x30a40,0xa0000},{0x101c3,0x600100},{0x2340243,0x10d0405},{0x7401c3,0x10e0401},{0x70a40,0xa0000},{0x2350243,0x10d0505},{0x29d0243,0x10d0506},{0x2368223,0x10d0705},{0x2370223,0x10d0805},{0x2378213,0x10d0905},{0x70224,0x1000805},{0x78214,0x1000905},{0x5,0x0},{0x40244,0x1000405},{0x50244,0x1000505},{0x60224,0x1000605},{0x68224,0x1000705}},
    {{0x4f20,0xa0000},{0xc920,0xa0000},{0x341,0xa0000},{0x14db0,0xa0000},{0x20041,0xa0000},{0x20ac0,0xa0000},{0x30241,0xa0000},{0x502c1,0xa0000},{0x30ac0,0xa0000},{0x10243,0x600100},{0x29c0043,0x10d0406},{0x740243,0x10e0401},{0x70ac0,0xa0000},{0x29d0043,0x10d0506},{0x70042,0xa0000},{0x29e0023,0x10d0606},{0x29e8023,0x10d0706},{0x29f0023,0x10d0806},{0x29f8013,0x10d0906},{0x70024,0x1000806},{0x78014,0x1000906},{0x5,0x0},{0x40044,0x1000406},{0x50044,0x1000506},{0x60024,0x1000606},{0x68024,0x1000706}},
    {{0x4fa0,0xa0000},{0xc9a0,0xa0000},{0x3c1,0xa0000},{0x14e30,0xa0000},{0x200c1,0xa0000},{0x20b40,0xa0000},{0x302c1,0xa0000},{0x50341,0xa0000},{0x30b40,0xa0000},{0x60041,0xa0000},{0x70341,0xa0000},{0x40640,0xa0000},{0x41340,0xa0000},{0x50340,0xa0000},{0x50dc0,0xa0000},{0x30043,0x600300},{0x29e00a3,0x10d0606},{0x29e80a3,0x10d0706},{0x29f00a3,0x10d0806},{0x29f8093,0x10d0906},{0x700a4,0x1000806},{0x78094,0x1000906},{0x5,0x0},{0x400c4,0x1000406},{0x500c4,0x1000506},{0x600a4,0x1000606},{0x680a4,0x1000706}},
    {{0x5020,0xa0000},{0xca20,0xa0000},{0x441,0xa0000},{0x14eb0,0xa0000},{0x20141,0xa0000},{0x20bc0,0xa0000},{0x30341,0xa0000},{0x503c1,0xa0000},{0x30bc0,0xa0000},{0x600c1,0xa0000},{0x703c1,0xa0000},{0x406c0,0xa0000},{0x413c0,0xa0000},{0x503c0,0xa0000},{0x50e40,0xa0000},{0x300c3,0x600300},{0x29e0123,0x10d0606},{0x29e8123,0x10d0706},{0x29f0123,0x10d0806},{0x29f8113,0x10d0906},{0x70124,0x1000806},{0x78114,0x1000906},{0x5,0x0},{0x40144,0x1000406},{0x50144,0x1000506},{0x60124,0x1000606},{0x68124,0x1000706}},
    {{0x50a0,0xa0000},{0xcaa0,0xa0000},{0x4c1,0xa0000},{0x14f30,0xa0000},{0x201c1,0xa0000},{0x20c40,0xa0000},{0x303c1,0xa0000},{0x50441,0xa0000},{0x30c40,0xa0000},{0x60141,0xa0000},{0x70441,0xa0000},{0x40740,0xa0000},{0x41440,0xa0000},{0x50440,0xa0000},{0x50ec0,0xa0000},{0x30143,0x600300},{0x29e01a3,0x10d0606},{0x29e81a3,0x10d0706},{0x29f01a3,0x10d0806},{0x29f8193,0x10d0906},{0x701a4,0x1000806},{0x78194,0x1000906},{0x5,0x0},{0x401c4,0x1000406},{0x501c4,0x1000506},{0x601a4,0x1000606},{0x681a4,0x1000706}},
    {{0x5120,0xa0000},{0xcb20,0xa0000},{0x541,0xa0000},{0x14fb0,0xa0000},{0x20241,0xa0000},{0x20cc0,0xa0000},{0x30441,0xa0000},{0x504c1,0xa0000},{0x30cc0,0xa0000},{0x601c1,0xa0000},{0x704c1,0xa0000},{0x407c0,0xa0000},{0x414c0,0xa0000},{0x504c0,0xa0000},{0x50f40,0xa0000},{0x301c3,0x600300},{0x29e0223,0x10d0606},{0x29e8223,0x10d0706},{0x29f0223,0x10d0806},{0x29f8213,0x10d0906},{0x70224,0x1000806},{0x78214,0x1000906},{0x5,0x0},{0x40244,0x1000406},{0x50244,0x1000506},{0x60224,0x1000606},{0x68224,0x1000706}},
    {{0x51a0,0xa0000},{0xcba0,0xa0000},{0x5c1,0xa0000},{0x15030,0xa0000},{0x202c1,0xa0000},{0x20d40,0xa0000},{0x304c1,0xa0000},{0x50541,0xa0000},{0x30d40,0xa0000},{0x60241,0xa0000},{0x70541,0xa0000},{0x40840,0xa0000},{0x41540,0xa0000},{0x50540,0xa0000},{0x50fc0,0xa0000},{0x30243,0x600300},{0x760023,0x10e0601},{0x68023,0x10e0700},{0x70124,0x1000801},{0x701a4,0x1000802},{0x78014,0x1000900},{0x5,0x0}},
}};
#define D8(i) "+f"(d[i]), "+f"(d[i + 1]), "+f"(d[i + 2]), "+f"(d[i + 3]), "+f"(d[i + 4]), "+f"(d[i + 5]), "+f"(d[i + 6]), "+f"(d[i + 7])
template <int N> __device__ __forceinline__ void wgmma_side(float* d, uint32_t alo, uint32_t blo, int sc);
template <> __device__ __forceinline__ void wgmma_side<64>(float* d, uint32_t alo, uint32_t blo, int sc) {
    asm volatile("{.reg .pred p; .reg .b64 ad, bd; setp.ne.b32 p, %34, 0; mov.b64 ad, {%32, 0x40000040}; mov.b64 bd, {%33, 0x40000040};\n"
                 "wgmma.mma_async.sync.aligned.m64n64k16.f32.bf16.bf16 "
                 "{%0,%1,%2,%3,%4,%5,%6,%7,%8,%9,%10,%11,%12,%13,%14,%15,%16,%17,%18,%19,%20,%21,%22,%23,%24,%25,%26,%27,%28,%29,%30,%31},"
                 " ad, bd, p, 1, 1, 1, 0;}"
                 : D8(0), D8(8), D8(16), D8(24)
                 : "r"(alo), "r"(blo), "r"(sc));
}
template <> __device__ __forceinline__ void wgmma_side<128>(float* d, uint32_t alo, uint32_t blo, int sc) {
    asm volatile("{.reg .pred p; .reg .b64 ad, bd; setp.ne.b32 p, %66, 0; mov.b64 ad, {%64, 0x40000040}; mov.b64 bd, {%65, 0x40000040};\n"
                 "wgmma.mma_async.sync.aligned.m64n128k16.f32.bf16.bf16 "
                 "{%0,%1,%2,%3,%4,%5,%6,%7,%8,%9,%10,%11,%12,%13,%14,%15,%16,%17,%18,%19,%20,%21,%22,%23,%24,%25,%26,%27,%28,%29,%30,%31,"
                 "%32,%33,%34,%35,%36,%37,%38,%39,%40,%41,%42,%43,%44,%45,%46,%47,%48,%49,%50,%51,%52,%53,%54,%55,%56,%57,%58,%59,%60,%61,%62,%63},"
                 " ad, bd, p, 1, 1, 1, 0;}"
                 : D8(0), D8(8), D8(16), D8(24), D8(32), D8(40), D8(48), D8(56)
                 : "r"(alo), "r"(blo), "r"(sc));
}
template <> __device__ __forceinline__ void wgmma_side<192>(float* d, uint32_t alo, uint32_t blo, int sc) {
    asm volatile("{.reg .pred p; .reg .b64 ad, bd; setp.ne.b32 p, %98, 0; mov.b64 ad, {%96, 0x40000040}; mov.b64 bd, {%97, 0x40000040};\n"
                 "wgmma.mma_async.sync.aligned.m64n192k16.f32.bf16.bf16 "
                 "{%0,%1,%2,%3,%4,%5,%6,%7,%8,%9,%10,%11,%12,%13,%14,%15,%16,%17,%18,%19,%20,%21,%22,%23,%24,%25,%26,%27,%28,%29,%30,%31,"
                 "%32,%33,%34,%35,%36,%37,%38,%39,%40,%41,%42,%43,%44,%45,%46,%47,%48,%49,%50,%51,%52,%53,%54,%55,%56,%57,%58,%59,%60,%61,%62,%63,"
                 "%64,%65,%66,%67,%68,%69,%70,%71,%72,%73,%74,%75,%76,%77,%78,%79,%80,%81,%82,%83,%84,%85,%86,%87,%88,%89,%90,%91,%92,%93,%94,%95},"
                 " ad, bd, p, 1, 1, 1, 0;}"
                 : D8(0), D8(8), D8(16), D8(24), D8(32), D8(40), D8(48), D8(56), D8(64), D8(72), D8(80), D8(88)
                 : "r"(alo), "r"(blo), "r"(sc));
}
template <> __device__ __forceinline__ void wgmma_side<256>(float* d, uint32_t alo, uint32_t blo, int sc) {
    asm volatile("{.reg .pred p; .reg .b64 ad, bd; setp.ne.b32 p, %130, 0; mov.b64 ad, {%128, 0x40000040}; mov.b64 bd, {%129, 0x40000040};\n"
                 "wgmma.mma_async.sync.aligned.m64n256k16.f32.bf16.bf16 "
                 "{%0,%1,%2,%3,%4,%5,%6,%7,%8,%9,%10,%11,%12,%13,%14,%15,%16,%17,%18,%19,%20,%21,%22,%23,%24,%25,%26,%27,%28,%29,%30,%31,"
                 "%32,%33,%34,%35,%36,%37,%38,%39,%40,%41,%42,%43,%44,%45,%46,%47,%48,%49,%50,%51,%52,%53,%54,%55,%56,%57,%58,%59,%60,%61,%62,%63,"
                 "%64,%65,%66,%67,%68,%69,%70,%71,%72,%73,%74,%75,%76,%77,%78,%79,%80,%81,%82,%83,%84,%85,%86,%87,%88,%89,%90,%91,%92,%93,%94,%95,"
                 "%96,%97,%98,%99,%100,%101,%102,%103,%104,%105,%106,%107,%108,%109,%110,%111,%112,%113,%114,%115,%116,%117,%118,%119,%120,%121,%122,%123,%124,%125,%126,%127},"
                 " ad, bd, p, 1, 1, 1, 0;}"
                 : D8(0), D8(8), D8(16), D8(24), D8(32), D8(40), D8(48), D8(56), D8(64), D8(72), D8(80), D8(88), D8(96), D8(104), D8(112), D8(120)
                 : "r"(alo), "r"(blo), "r"(sc));
}
#define W8(i) "=f"(d[i]), "=f"(d[i + 1]), "=f"(d[i + 2]), "=f"(d[i + 3]), "=f"(d[i + 4]), "=f"(d[i + 5]), "=f"(d[i + 6]), "=f"(d[i + 7])
__device__ __forceinline__ void wgmma_first(float* d, uint32_t alo, uint32_t blo) {
    asm volatile("{.reg .pred p; .reg .b64 ad, bd; setp.ne.b32 p, %130, 0; mov.b64 ad, {%128, 0x40000040}; mov.b64 bd, {%129, 0x40000040};\n"
                 "wgmma.mma_async.sync.aligned.m64n256k16.f32.bf16.bf16 "
                 "{%0,%1,%2,%3,%4,%5,%6,%7,%8,%9,%10,%11,%12,%13,%14,%15,%16,%17,%18,%19,%20,%21,%22,%23,%24,%25,%26,%27,%28,%29,%30,%31,"
                 "%32,%33,%34,%35,%36,%37,%38,%39,%40,%41,%42,%43,%44,%45,%46,%47,%48,%49,%50,%51,%52,%53,%54,%55,%56,%57,%58,%59,%60,%61,%62,%63,"
                 "%64,%65,%66,%67,%68,%69,%70,%71,%72,%73,%74,%75,%76,%77,%78,%79,%80,%81,%82,%83,%84,%85,%86,%87,%88,%89,%90,%91,%92,%93,%94,%95,"
                 "%96,%97,%98,%99,%100,%101,%102,%103,%104,%105,%106,%107,%108,%109,%110,%111,%112,%113,%114,%115,%116,%117,%118,%119,%120,%121,%122,%123,%124,%125,%126,%127},"
                 " ad, bd, p, 1, 1, 1, 0;}"
                 : W8(0), W8(8), W8(16), W8(24), W8(32), W8(40), W8(48), W8(56), W8(64), W8(72), W8(80), W8(88), W8(96), W8(104), W8(112), W8(120)
                 : "r"(alo), "r"(blo), "n"(0));
}
#undef W8
#undef D8

__device__ __forceinline__ void bulk_st(void* dst, uint32_t src, uint32_t bytes) {
    asm volatile("cp.async.bulk.global.shared::cta.bulk_group [%0], [%1], %2;" :: "l"(dst), "r"(src), "r"(bytes) : "memory");
}
__device__ __forceinline__ void red_release(uint32_t* p, uint32_t v) { asm volatile("red.release.gpu.global.add.u32 [%0], %1;" :: "l"(p), "r"(v) : "memory"); }
__device__ __forceinline__ void wait_ge(const uint32_t* p, uint32_t v) { for (int c = 0; c < SPIN_LIM && (int)(ld_acquire(p) - v) < 0; c++) { } }
__device__ __forceinline__ uint4* part_ptr(Job job, int wg) {
    return g_op + (size_t)((job.x >> 13) & 63) * (10 * NKS * 256) + (((job.x >> 7) & 63) * 2 + wg) * NKS * ((job.x >> 3) & 15) * 256;
}

template <int T>
__device__ __forceinline__ void side_job(Job job, uint32_t& it, uint32_t& n, uint32_t sb, uint32_t sa, int wg, int t)
{
    float acc[T / 2];
    const int nkb = job.y >> 16 & 255;
    constexpr uint32_t NS = T == 64 ? 2 * SST : SST, SZ = SST * S_STAGE / NS, BO = T == 64 ? SB_FINE : 0;
    constexpr bool peel = T == 256;
    uint32_t prev = 0;
    auto block = [&](int kb, auto FIRST) {
        const uint32_t st = it % NS;
        const uint32_t alo = ((sb + st * SZ + wg * 8192) >> 4) | (64u << 16), blo = ((sb + st * SZ + 16384) >> 4) | (1u << 16);
        mbar_wait_long(sb + SB_FULL + BO + 8 * st, (it / NS) & 1);
        wg_fence();
        if constexpr (FIRST.value) wgmma_first(acc, alo, blo);
#pragma unroll
        for (int k4 = FIRST.value; k4 < 4; k4++) wgmma_side<T>(acc, alo + k4 * 128, blo + k4 * 2, peel ? 1 : kb | k4);
        wg_commit();
        if (peel ? !FIRST.value : kb) { wg_wait<1>(); arrive_e(prev); }
        prev = sb + SB_EMPTY + BO + 8 * st;
        it++;
    };
    if constexpr (peel) block(0, IC<1>());
    else {
#pragma unroll
        for (int i = 0; i < T / 2; i++) acc[i] = 0.f;
    }
    for (int kb = peel; kb < nkb; kb++) block(kb, IC<0>());
    if (n) mbar_wait_long(sb + SB_FREE, (n - 1) & 1);
    n++;
    wg_wait<0>();
    arrive_e(prev);
    const bool raw = (job.x & 7) == JV || job.y >> 24;
#pragma unroll
    for (int u = 0; u < T / 16; u++) {
        const uint4 w = make_uint4(pack2(acc[8 * u], acc[8 * u + 1]), pack2(acc[8 * u + 2], acc[8 * u + 3]),
                                   pack2(acc[8 * u + 4], acc[8 * u + 5]), pack2(acc[8 * u + 6], acc[8 * u + 7]));
        if (raw || T != 256) sts4(sb + S_STG + wg * 32768 + t * 16 + u * 2048, make_uint4(w.x, w.z, w.y, w.w));
        else stsm4t(sb + S_STG + wg * 32768 + sa + u * 2048, w.x, w.y, w.z, w.w);
    }
    __syncwarp();
    arrive_e(sb + SB_STAGED + 8 * wg);
}

__device__ __forceinline__ void ld20(const bf16* p, uint32_t* w) {
#pragma unroll
    for (int i = 0; i < 5; i++) asm volatile("ld.global.v2.b32 {%0,%1}, [%2];" : "=r"(w[2 * i]), "=r"(w[2 * i + 1]) : "l"(p + 4 * i) : "memory");
}

__global__ void __launch_bounds__(384, 1) side_kernel(const __grid_constant__ SideParams P)
{
    extern __shared__ __align__(1024) uint8_t smem[];
    const uint32_t sb = smem_u32(smem);
    const int tid = threadIdx.x, lane = tid & 31;
    const int warp = __shfl_sync(0xffffffffu, tid >> 5, 0);
    if (tid == 0) {
        for (int i = 0; i < SST; i++) { mbar_init(sb + SB_FULL + 8 * i, 1); mbar_init(sb + SB_EMPTY + 8 * i, 8); }
        for (int i = 0; i < 2 * SST; i++) { mbar_init(sb + SB_FULL + SB_FINE + 8 * i, 1); mbar_init(sb + SB_EMPTY + SB_FINE + 8 * i, 8); }
        mbar_init(sb + SB_STAGED, 4); mbar_init(sb + SB_STAGED + 8, 4); mbar_init(sb + SB_FREE, 1);
        asm volatile("fence.mbarrier_init.release.cluster;" ::: "memory");
    }
    __syncthreads();
    const Job* jobs = c_jobs.j[blockIdx.x];
    if (warp < 8) {
        asm volatile("setmaxnreg.inc.sync.aligned.u32 192;");
        const uint32_t ep = ld_epoch();
        uint32_t it = 0, it2 = 0, n = 0;
        const int wg = warp >> 2, t = tid & 127;
        const uint32_t sa = ((lane & 7) + ((lane >> 4) << 3)) * 128 + (((2 * (t >> 5) + ((lane >> 3) & 1)) ^ (lane & 7)) << 4);
        for (int j = 0; ; j++) {
            const Job job = jobs[j];
            const int type = job.x & 7, nb = (job.x >> 3) & 15;
            if (type == JEND) break;
            if (type == JR) {
                const int ks = job.y & 15, ct = (job.x >> 7) & 63;
                if (t == 0) {
                    asm volatile("cp.async.bulk.wait_group.read 0;" ::: "memory");
                    wait_ge(g_cnt + CNT_O + (job.y >> 8 & 255) * 5 + ct, ep * NKS);
                }
                bar_sync(1 + wg, 128);
                const uint4* part = part_ptr(job, wg) + ks * 128 + t;
                const uint32_t rs = sb + S_RST + wg * 6144;
                uint4 q[3][NKS];
#pragma unroll
                for (int i = 0; i < 3; i++) {
#pragma unroll
                    for (int k = 0; k < NKS; k++) q[i][k] = make_uint4(0, 0, 0, 0);
                    if (ks + i * NKS < 2 * nb) {
#pragma unroll
                        for (int k = 0; k < NKS; k++) q[i][k] = ld_pkt(part + k * nb * 256 + i * NKS * 128);
                    }
                }
#pragma unroll
                for (int i = 0; i < 3; i++)
                    if (ks + i * NKS < 2 * nb) {
                        float r[8] = {0, 0, 0, 0, 0, 0, 0, 0};
#pragma unroll
                        for (int k = 0; k < NKS; k++) {
                            r[0] += bf_lo(q[i][k].x); r[1] += bf_hi(q[i][k].x); r[2] += bf_lo(q[i][k].y); r[3] += bf_hi(q[i][k].y);
                            r[4] += bf_lo(q[i][k].z); r[5] += bf_hi(q[i][k].z); r[6] += bf_lo(q[i][k].w); r[7] += bf_hi(q[i][k].w);
                        }
                        stsm4t(rs + sa + i * 2048, pack2(r[0], r[1]), pack2(r[4], r[5]), pack2(r[2], r[3]), pack2(r[6], r[7]));
                    }
                asm volatile("fence.proxy.async.shared::cta;" ::: "memory");
                bar_sync(1 + wg, 128);
                if (t == 0) {
                    for (int i = 0; i < 3; i++)
                        if (ks + i * NKS < 2 * nb) tma_st(&P.sto, rs + i * 2048, DM + ct * 128 + wg * 64, ((job.x >> 13) & 63) * 32 + (ks + i * NKS) * 16);
                    asm volatile("cp.async.bulk.commit_group;" ::: "memory");
                }
                __syncwarp();
                continue;
            }
            switch (nb) {
                case 8: side_job<256>(job, it, n, sb, sa, wg, t); break;
                case 6: side_job<192>(job, it, n, sb, sa, wg, t); break;
                case 4: side_job<128>(job, it, n, sb, sa, wg, t); break;
                default: side_job<64>(job, it2, n, sb, sa, wg, t); break;
            }
        }
        if (t == 0) asm volatile("cp.async.bulk.wait_group 0;" ::: "memory");
    } else {
        asm volatile("setmaxnreg.dec.sync.aligned.u32 120;");
        if (warp == 8) {
            uint32_t ep = 0, ns = SST, sz = S_STAGE, bo = sb, sa = 0, pa = 1, sl = 0;
            for (int j = 0; ; j++) {
                const Job job = jobs[j];
                const int type = job.x & 7;
                if (type == JEND) break;
                if (type == JR) continue;
                const int nb = (job.x >> 3) & 15, c0 = ((job.x >> 7) & 63) * 2, seg0 = (job.x >> 13) & 63, kb0 = (job.x >> 19) & 127,
                          nkb = job.y >> 16 & 255;
                const CUtensorMap *ta = &P.a[type], *tb = nb == 8 ? &P.b[type] : &P.c[(type == JV ? 3 : 4) - nb / 2];
                auto ready = [&]() {
                    bool ok = true;
                    if (type == JP) ok = (int)(ld_acquire(g_cnt + CNT_ATT + (seg0 >> 3)) - ep * 256) >= 0;
                    else
                        for (int i = 0; i < nkb; i += 32) ok &= (int)(ld_acquire(g_prog + kb0 + min(i + lane, nkb - 1)) - (ep * 128 + seg0 + nb)) >= 0;
                    return __all_sync(0xffffffffu, ok);
                };
                if (nb == 2 && ns == SST) {
                    for (uint32_t i = 0; i < SST; i++) mbar_wait_long(sb + SB_EMPTY + 8 * i, pa ^ (i < sa));
                    ns = 2 * SST; sz = S_STAGE / 2; bo = sb + SB_FINE; sa = 0; pa = 1; sl = 0;
                }
                auto loadA = [&](int kb) {
                    const uint32_t full = bo + SB_FULL + 8 * sa;
                    mbar_wait_long(bo + SB_EMPTY + 8 * sa, pa);
                    expect_e(full, 16384 + nb * 4096);
                    tma3d_e(sb + sa * sz, ta, (kb0 + kb) * 64, c0, full);
                    if (++sa == ns) { sa = 0; pa ^= 1; }
                };
                auto loadB = [&](int kb) {
                    tma2d_e(sb + sl * sz + 16384, tb, (kb0 + kb) * 64, seg0 * 32, bo + SB_FULL + 8 * sl);
                    if (++sl == ns) sl = 0;
                };
                int pre = 0;
                if (type >= JP) {
                    if (!ready()) {
                        pre = ns;
#pragma unroll 1
                        for (int kb = 0; kb < pre; kb++) loadA(kb);
                        for (int c = 0; c < SPIN_LIM && !ready(); c++) { }
                    }
                    asm volatile("fence.proxy.async.global;" ::: "memory");
                }
#pragma unroll 1
                for (int kb = 0; kb < nkb; kb++) { if (kb >= pre) loadA(kb); loadB(kb); }
                if (j == 0) ep = ld_epoch();
            }
            if (blockIdx.x == 0 && lane == 0) g_epoch = ep;
        } else if (warp == 9) {
            if (lane == 0) {
                const uint32_t ep = ld_epoch();
                uint32_t n = 0;
                for (int j = 0; ; j++) {
                    const Job job = jobs[j];
                    const int type = job.x & 7;
                    if (type == JEND) break;
                    if (type == JR) continue;
                    const int nb = (job.x >> 3) & 15, ct = (job.x >> 7) & 63, seg0 = (job.x >> 13) & 63;
                    for (int wg = 0; wg < 2; wg++) {
                        const uint32_t src = sb + S_STG + wg * 32768;
                        mbar_wait_long(sb + SB_STAGED + 8 * wg, n & 1);
                        asm volatile("fence.proxy.async.shared::cta;" ::: "memory");
                        if (type == JV) bulk_st(g_vx + ((ct * 2 + wg) * 64 + seg0) * 256, src, nb * 4096);
                        else if (job.y >> 24) bulk_st(part_ptr(job, wg) + (job.y & 15) * nb * 256, src, nb * 4096);
                        else tma_st(&P.st[type != JQ], src, (type == JO ? DM : 0) + ct * 128 + wg * 64, seg0 * 32);
                    }
                    asm volatile("cp.async.bulk.commit_group;" ::: "memory");
                    asm volatile("cp.async.bulk.wait_group.read 0;" ::: "memory");
                    mbar_arrive(sb + SB_FREE);
                    asm volatile("cp.async.bulk.wait_group 0;" ::: "memory");
                    if (type == JV) { st_release(g_flagv + ct * 128 + seg0, ep); g_flagv[ct * 128 + 64 + seg0] = ep; }
                    if (type == JQ) red_release(g_cnt + CNT_Q + (seg0 >> 3), 1);
                    if (job.y >> 24) red_release(g_cnt + CNT_O + (job.y >> 8 & 255) * 5 + ct, 1);
                    n++;
                }
            }
        } else {
            const uint32_t ep = ld_epoch();
            const float scl = 0.22360679774997896f * 1.4426950408889634f;
            for (int p = blockIdx.x * 2 + warp - 10; p < SEQ / 2; p += 2 * NSIDE) {
                const int t0 = 4 * (p >> 1) + (p & 1);
                wait_ge(g_cnt + CNT_Q + (max(t0 - 14, 0) >> 8), ep * 15);
                wait_ge(g_cnt + CNT_Q + (t0 >> 8), ep * 15);
                const bf16* base = g_qkvA + lane * 20;
                uint32_t w[18][10];
                auto row = [&](int j) { if (j < 18) ld20(base + (size_t)max(t0 + 2 - 2 * (j % 9), 0) * 1920 + (j < 9 ? 640 : 1280), w[j]); };
                float l0[8], l1[8];
                {
                    uint32_t u0[10], u1[10];
                    float q0[20], q1[20];
                    ld20(base + (size_t)t0 * 1920, u0); ld20(base + (size_t)(t0 + 2) * 1920, u1);
                    row(0); row(1);
#pragma unroll
                    for (int i = 0; i < 10; i++) { q0[2 * i] = bf_lo(u0[i]); q0[2 * i + 1] = bf_hi(u0[i]); q1[2 * i] = bf_lo(u1[i]); q1[2 * i + 1] = bf_hi(u1[i]); }
#pragma unroll
                    for (int j = 0; j < 9; j++) {
                        row(j + 2);
                        blk(warp);
                        float a0 = 0.f, a1 = 0.f;
#pragma unroll
                        for (int i = 0; i < 10; i++) {
                            const float lo = bf_lo(w[j][i]), hi = bf_hi(w[j][i]);
                            if (j > 0) a0 = fmaf(q0[2 * i + 1], hi, fmaf(q0[2 * i], lo, a0));
                            if (j < 8) a1 = fmaf(q1[2 * i + 1], hi, fmaf(q1[2 * i], lo, a1));
                        }
                        const bool in = t0 + 2 - 2 * j >= 0;
                        if (j > 0) l0[j - 1] = in ? a0 * scl : -3.0e38f;
                        if (j < 8) l1[j] = in ? a1 * scl : -3.0e38f;
                    }
                }
                float m0 = l0[0], m1 = l1[0], s0 = 0.f, s1 = 0.f;
#pragma unroll
                for (int j = 1; j < 8; j++) { m0 = fmaxf(m0, l0[j]); m1 = fmaxf(m1, l1[j]); }
#pragma unroll
                for (int j = 0; j < 8; j++) { l0[j] = ex2(l0[j] - m0); s0 += l0[j]; l1[j] = ex2(l1[j] - m1); s1 += l1[j]; }
                float o0[20], o1[20];
#pragma unroll
                for (int i = 0; i < 20; i++) o0[i] = o1[i] = 0.f;
#pragma unroll
                for (int j = 0; j < 9; j++) {
                    row(j + 11);
                    blk(warp);
#pragma unroll
                    for (int i = 0; i < 10; i++) {
                        const float lo = bf_lo(w[9 + j][i]), hi = bf_hi(w[9 + j][i]);
                        if (j > 0) { o0[2 * i] = fmaf(l0[j - 1], lo, o0[2 * i]); o0[2 * i + 1] = fmaf(l0[j - 1], hi, o0[2 * i + 1]); }
                        if (j < 8) { o1[2 * i] = fmaf(l1[j], lo, o1[2 * i]); o1[2 * i + 1] = fmaf(l1[j], hi, o1[2 * i + 1]); }
                    }
                }
                s0 = 1.f / s0; s1 = 1.f / s1;
                uint2* dst = reinterpret_cast<uint2*>(g_oA + (size_t)t0 * DM + lane * 20);
#pragma unroll
                for (int i = 0; i < 5; i++) {
                    dst[i] = make_uint2(pack2(o0[4 * i] * s0, o0[4 * i + 1] * s0), pack2(o0[4 * i + 2] * s0, o0[4 * i + 3] * s0));
                    dst[i + 2 * DM / 4] = make_uint2(pack2(o1[4 * i] * s1, o1[4 * i + 1] * s1), pack2(o1[4 * i + 2] * s1, o1[4 * i + 3] * s1));
                }
                __syncwarp();
                if (lane == 0) red_release(g_cnt + CNT_ATT + (t0 >> 8), 2);
            }
            int j = 0;
            while ((jobs[j].x & 7) != JEND) j++;
            for (j++; (jobs[j].x & 7) == JR; j++) {
                const Job job = jobs[j];
                const int nb = (job.x >> 3) & 15, ct = (job.x >> 7) & 63;
                for (int c = 0; c < SPIN_LIM && (int)(ld_acquire(g_cnt + CNT_O + (job.y >> 8 & 255) * 5 + ct) - ep * NKS) < 0; c++) __nanosleep(200);
                for (int u = job.y & 15; u < 2 * nb; u += NKS) {
                    const uint4* part = part_ptr(job, warp - 10) + u * 128 + lane;
                    bf16* op = P.out + (size_t)(((job.x >> 13) & 63) * 32 + u * 16 + (lane >> 2)) * OUTW + DM + ct * 128 + (warp - 10) * 64 + (lane & 1) * 8 + (lane & 2) * 2;
#pragma unroll 1
                    for (int h = 0; h < 2; h++) {
                        uint4 q[2][NKS];
#pragma unroll
                        for (int i = 0; i < 2; i++)
#pragma unroll
                            for (int k = 0; k < NKS; k++) q[i][k] = ld_pkt(part + k * nb * 256 + (2 * h + i) * 32);
#pragma unroll
                        for (int i = 0; i < 2; i++) {
                            float r[8] = {0, 0, 0, 0, 0, 0, 0, 0};
#pragma unroll
                            for (int k = 0; k < NKS; k++) {
                                r[0] += bf_lo(q[i][k].x); r[1] += bf_hi(q[i][k].x); r[2] += bf_lo(q[i][k].y); r[3] += bf_hi(q[i][k].y);
                                r[4] += bf_lo(q[i][k].z); r[5] += bf_hi(q[i][k].z); r[6] += bf_lo(q[i][k].w); r[7] += bf_hi(q[i][k].w);
                            }
#pragma unroll
                            for (int m = 0; m < 2; m++) {
                                const uint32_t a = movm(pack2(r[2 * m], r[2 * m + 1])), b = movm(pack2(r[4 + 2 * m], r[5 + 2 * m]));
                                const uint32_t o = __shfl_xor_sync(0xffffffffu, lane & 1 ? a : b, 1);
                                *reinterpret_cast<uint2*>(op + m * 8 * OUTW + (2 * h + i) * 16) = lane & 1 ? make_uint2(o, b) : make_uint2(a, o);
                            }
                        }
                    }
                }
            }
        }
    }
}

typedef CUresult (*EncodeFn)(CUtensorMap*, CUtensorMapDataType, cuuint32_t, void*, const cuuint64_t*, const cuuint64_t*,
                             const cuuint32_t*, const cuuint32_t*, CUtensorMapInterleave, CUtensorMapSwizzle,
                             CUtensorMapL2promotion, CUtensorMapFloatOOBfill);
static void make_map(EncodeFn enc, CUtensorMap* tm, const void* ptr, uint64_t cols, uint64_t rows, uint32_t bc, uint32_t br) {
    cuuint64_t dims[2] = {cols, rows}, strides[1] = {cols * 2};
    cuuint32_t box[2] = {bc, br}, es[2] = {1, 1};
    enc(tm, CU_TENSOR_MAP_DATA_TYPE_BFLOAT16, 2, const_cast<void*>(ptr), dims, strides, box, es, CU_TENSOR_MAP_INTERLEAVE_NONE,
        bc == 64 ? CU_TENSOR_MAP_SWIZZLE_128B : CU_TENSOR_MAP_SWIZZLE_64B,
        CU_TENSOR_MAP_L2_PROMOTION_L2_128B, CU_TENSOR_MAP_FLOAT_OOB_FILL_NONE);
}

static void make_map3(EncodeFn enc, CUtensorMap* tm, const void* ptr, uint64_t cols, uint64_t rows, uint32_t br, uint32_t nb, uint32_t bc = 64) {
    cuuint64_t dims[3] = {bc, rows, cols / bc}, strides[2] = {cols * 2, bc * 2};
    cuuint32_t box[3] = {bc, br, nb}, es[3] = {1, 1, 1};
    enc(tm, CU_TENSOR_MAP_DATA_TYPE_BFLOAT16, 3, const_cast<void*>(ptr), dims, strides, box, es, CU_TENSOR_MAP_INTERLEAVE_NONE,
        bc == 64 ? CU_TENSOR_MAP_SWIZZLE_128B : CU_TENSOR_MAP_SWIZZLE_64B,
        CU_TENSOR_MAP_L2_PROMOTION_L2_128B, CU_TENSOR_MAP_FLOAT_OOB_FILL_NONE);
}

extern "C" void kernel_launch(void* const* d_in, const int* in_sizes, int n_in, void* d_out, int out_size) {
    (void)in_sizes; (void)n_in; (void)out_size;
    const bf16* A_x = (const bf16*)d_in[0];
    const bf16* A_wqkv = (const bf16*)d_in[1];
    const bf16* A_wo = (const bf16*)d_in[2];
    const bf16* B_x = (const bf16*)d_in[3];
    const bf16* B_mem0 = (const bf16*)d_in[4];
    const bf16* B_Wq = (const bf16*)d_in[5];
    const bf16* B_Wk = (const bf16*)d_in[6];
    const bf16* B_Wv = (const bf16*)d_in[7];
    const bf16* B_Wo = (const bf16*)d_in[8];
    bf16* out = (bf16*)d_out;

    static EncodeFn enc = nullptr;
    static void *p_ox, *p_qkv, *p_oA, *p_xch;
    if (!enc) {
        void* fn = nullptr; cudaDriverEntryPointQueryResult qr;
        cudaGetDriverEntryPoint("cuTensorMapEncodeTiled", &fn, cudaEnableDefault, &qr);
        enc = (EncodeFn)fn;
        cudaFuncSetAttribute(chain_kernel, cudaFuncAttributeMaxDynamicSharedMemorySize, CHAIN_SMEM);
        cudaFuncSetAttribute(side_kernel, cudaFuncAttributeMaxDynamicSharedMemorySize, SIDE_SMEM);
        cudaGetSymbolAddress(&p_ox, g_ox); cudaGetSymbolAddress(&p_qkv, g_qkvA); cudaGetSymbolAddress(&p_oA, g_oA);
        cudaGetSymbolAddress(&p_xch, g_xch);
    }
    CUtensorMap tmXA, tmXB, tmWq, tmWk, tmWv, tmWo, tmOx;
    make_map3(enc, &tmXA, B_x, DM, SEQ, 32, NX);
    make_map3(enc, &tmXB, B_x, DM, SEQ, 32, 1);
    make_map(enc, &tmWq, B_Wq, HE, DM, 64, 128);
    make_map(enc, &tmWk, B_Wk, HE, DM, 64, 128);
    make_map(enc, &tmWv, B_Wv, HE, DM, 64, 128);
    make_map3(enc, &tmWo, B_Wo, DM, HE, 64, 7, 32);
    SideParams sp;
    sp.out = out;
    make_map3(enc, &sp.a[JV], B_Wv, HE, DM, 64, 2);
    make_map3(enc, &sp.a[JQ], A_wqkv, 3 * DM, DM, 64, 2);
    make_map3(enc, &sp.a[JP], A_wo, DM, DM, 64, 2);
    make_map3(enc, &sp.a[JO], B_Wo, DM, HE, 64, 2);
    const void* act[4] = {B_x, A_x, p_oA, p_ox};
    for (int i = 0; i < 4; i++) make_map(enc, &sp.b[i], act[i], i == JO ? HE : DM, SEQ, 64, 256);
    make_map(enc, &sp.c[0], B_x, DM, SEQ, 64, 192);
    make_map(enc, &sp.c[1], B_x, DM, SEQ, 64, 128);
    make_map(enc, &sp.c[2], p_ox, HE, SEQ, 64, 128);
    make_map(enc, &sp.c[3], p_ox, HE, SEQ, 64, 64);
    make_map(enc, &tmOx, p_ox, HE, SEQ, 64, 32);
    make_map(enc, &sp.st[0], p_qkv, 3 * DM, SEQ, 64, 256);
    make_map(enc, &sp.st[1], out, OUTW, SEQ, 64, 256);
    make_map(enc, &sp.sto, out, OUTW, SEQ, 64, 16);

    cudaStream_t st = cudaStreamPerThread;
    chain_kernel<<<96, 384, CHAIN_SMEM, st>>>(tmXA, tmXB, tmWq, tmWk, tmWv, tmWo, tmOx, B_mem0,
                                              (const char*)(((uintptr_t)p_xch + 0x1fffff) & ~(uintptr_t)0x1fffff), out);
    cudaLaunchConfig_t cfg = {};
    cfg.gridDim = dim3(NSIDE); cfg.blockDim = dim3(384); cfg.dynamicSmemBytes = SIDE_SMEM; cfg.stream = st;
    cudaLaunchAttribute at[1];
    at[0].id = cudaLaunchAttributeProgrammaticStreamSerialization; at[0].val.programmaticStreamSerializationAllowed = 1;
    cfg.attrs = at; cfg.numAttrs = 1;
    cudaLaunchKernelEx(&cfg, side_kernel, sp);
}
```

```cpp
#include <cuda_runtime.h>
#include <cuda_bf16.h>
#include <cuda.h>
#include <stdint.h>
#include <string.h>
#include <math.h>
#include <type_traits>

typedef __nv_bfloat16 bf16;

constexpr int SEQ = 2048, DM = 640, NH = 32, DH = 192, HE = NH * DH;
constexpr int NSEG = 64;
constexpr int OUTW = 1280;

__device__ uint4 g_xch[(4 << 20) / 16];
__device__ uint4 g_near4[96 * 4];
__device__ bf16  g_ox[SEQ * HE];
__device__ bf16  g_qkvA[SEQ * 3 * DM];
__device__ bf16  g_oA[SEQ * DM];
__device__ uint4 g_vx[96 * NSEG * 256];
__device__ uint4 g_op[NSEG * 70 * 256];
__device__ uint4 g_tail[2 * 32 * 80 * 32];
__device__ uint32_t g_epoch;
__device__ uint32_t g_flagv[96 * 64];
__device__ uint32_t g_prog[96];
__device__ uint32_t g_cnt[256];
constexpr int CNT_Q = 0, CNT_ATT = 8, CNT_O = 16, SPIN_LIM = 1 << 15;

__device__ __forceinline__ uint32_t smem_u32(const void* p) { return (uint32_t)__cvta_generic_to_shared(p); }
__device__ __forceinline__ uint32_t pack2(float lo, float hi) {
    uint32_t r; asm("cvt.rn.bf16x2.f32 %0, %1, %2;" : "=r"(r) : "f"(hi), "f"(lo)); return r;
}
__device__ __forceinline__ float ex2(float x) { float r; asm("ex2.approx.ftz.f32 %0, %1;" : "=f"(r) : "f"(x)); return r; }
__device__ __forceinline__ float rcpf(float x) { float r; asm("rcp.approx.ftz.f32 %0, %1;" : "=f"(r) : "f"(x)); return r; }
__device__ __forceinline__ void mbar_init(uint32_t bar, uint32_t cnt) {
    asm volatile("mbarrier.init.shared::cta.b64 [%0], %1;" :: "r"(bar), "r"(cnt) : "memory");
}
__device__ __forceinline__ void mbar_arrive(uint32_t bar) {
    asm volatile("mbarrier.arrive.shared::cta.b64 _, [%0];" :: "r"(bar) : "memory");
}
__device__ __forceinline__ void mbar_expect(uint32_t bar, uint32_t bytes) {
    asm volatile("mbarrier.arrive.expect_tx.shared::cta.b64 _, [%0], %1;" :: "r"(bar), "r"(bytes) : "memory");
}
constexpr int WAIT_LIM = 2048;
template <int N> __device__ __forceinline__ void mbar_wait_n(uint32_t bar, uint32_t parity) {
    asm volatile("{.reg .pred p, q; .reg .u32 c; mov.u32 c, %2;\n"
                 "WL_%=: sub.u32 c, c, 1; setp.eq.u32 q, c, 0; @q bra WD_%=; mbarrier.try_wait.parity.shared::cta.b64 p, [%0], %1;\n"
                 "@!p bra WL_%=; WD_%=: }" :: "r"(bar), "r"(parity), "n"(N) : "memory");
}
__device__ __forceinline__ void mbar_wait(uint32_t bar, uint32_t parity) { mbar_wait_n<1024>(bar, parity); }
__device__ __forceinline__ void mbar_wait_long(uint32_t bar, uint32_t parity) { mbar_wait_n<4096>(bar, parity); }
__device__ __forceinline__ void bar_sync(int id, int n) { asm volatile("bar.sync %0, %1;" :: "r"(id), "r"(n) : "memory"); }
__device__ __forceinline__ void bar_arrive(int id, int n) { asm volatile("bar.arrive %0, %1;" :: "r"(id), "r"(n) : "memory"); }
__device__ __forceinline__ void tma2d(uint32_t dst, const CUtensorMap* tm, int c0, int c1, uint32_t bar) {
    asm volatile("cp.async.bulk.tensor.2d.shared::cluster.global.mbarrier::complete_tx::bytes [%0], [%1, {%3, %4}], [%2];"
                 :: "r"(dst), "l"(tm), "r"(bar), "r"(c0), "r"(c1) : "memory");
}
__device__ __forceinline__ void tma_st(const CUtensorMap* tm, uint32_t src, int c0, int c1) {
    asm volatile("cp.async.bulk.tensor.2d.global.shared::cta.bulk_group [%0, {%2, %3}], [%1];" :: "l"(tm), "r"(src), "r"(c0), "r"(c1) : "memory");
}
__device__ __forceinline__ void ldsm4(uint32_t a, uint32_t& r0, uint32_t& r1, uint32_t& r2, uint32_t& r3) {
    asm volatile("ldmatrix.sync.aligned.m8n8.x4.shared.b16 {%0,%1,%2,%3}, [%4];"
                 : "=r"(r0), "=r"(r1), "=r"(r2), "=r"(r3) : "r"(a) : "memory");
}
__device__ __forceinline__ void ldsm4t(uint32_t a, uint32_t& r0, uint32_t& r1, uint32_t& r2, uint32_t& r3) {
    asm volatile("ldmatrix.sync.aligned.m8n8.x4.trans.shared.b16 {%0,%1,%2,%3}, [%4];"
                 : "=r"(r0), "=r"(r1), "=r"(r2), "=r"(r3) : "r"(a) : "memory");
}
__device__ __forceinline__ void ldsm2t(uint32_t a, uint32_t& r0, uint32_t& r1) {
    asm volatile("ldmatrix.sync.aligned.m8n8.x2.trans.shared.b16 {%0,%1}, [%2];" : "=r"(r0), "=r"(r1) : "r"(a) : "memory");
}
__device__ __forceinline__ void stsm4t(uint32_t a, uint32_t r0, uint32_t r1, uint32_t r2, uint32_t r3) {
    asm volatile("stmatrix.sync.aligned.m8n8.x4.trans.shared.b16 [%0], {%1,%2,%3,%4};"
                 :: "r"(a), "r"(r0), "r"(r1), "r"(r2), "r"(r3) : "memory");
}
__device__ __forceinline__ void stsm4(uint32_t a, uint32_t r0, uint32_t r1, uint32_t r2, uint32_t r3) {
    asm volatile("stmatrix.sync.aligned.m8n8.x4.shared.b16 [%0], {%1,%2,%3,%4};"
                 :: "r"(a), "r"(r0), "r"(r1), "r"(r2), "r"(r3) : "memory");
}
__device__ __forceinline__ void stsm2t(uint32_t a, uint32_t r0, uint32_t r1) {
    asm volatile("stmatrix.sync.aligned.m8n8.x2.trans.shared.b16 [%0], {%1,%2};" :: "r"(a), "r"(r0), "r"(r1) : "memory");
}
__device__ __forceinline__ uint32_t movm(uint32_t a) {
    uint32_t d; asm volatile("movmatrix.sync.aligned.m8n8.trans.b16 %0, %1;" : "=r"(d) : "r"(a)); return d;
}
__device__ __forceinline__ void mma16(float* c, uint32_t a0, uint32_t a1, uint32_t a2, uint32_t a3, uint32_t b0, uint32_t b1) {
    asm volatile("mma.sync.aligned.m16n8k16.row.col.f32.bf16.bf16.f32 {%0,%1,%2,%3}, {%4,%5,%6,%7}, {%8,%9}, {%0,%1,%2,%3};"
                 : "+f"(c[0]), "+f"(c[1]), "+f"(c[2]), "+f"(c[3]) : "r"(a0), "r"(a1), "r"(a2), "r"(a3), "r"(b0), "r"(b1));
}
__device__ __forceinline__ void mma8(float* c, uint32_t a0, uint32_t a1, uint32_t b0) {
    asm volatile("mma.sync.aligned.m16n8k8.row.col.f32.bf16.bf16.f32 {%0,%1,%2,%3}, {%4,%5}, {%6}, {%0,%1,%2,%3};"
                 : "+f"(c[0]), "+f"(c[1]), "+f"(c[2]), "+f"(c[3]) : "r"(a0), "r"(a1), "r"(b0));
}
__device__ __forceinline__ void wg_fence() { asm volatile("wgmma.fence.sync.aligned;" ::: "memory"); }
__device__ __forceinline__ void wg_commit() { asm volatile("wgmma.commit_group.sync.aligned;" ::: "memory"); }
template <int N> __device__ __forceinline__ void wg_wait() { asm volatile("wgmma.wait_group.sync.aligned %0;" :: "n"(N) : "memory"); }
__device__ __forceinline__ uint64_t mkdesc(uint32_t addr, uint32_t lbo, uint32_t sbo, uint32_t swz) {
    return (uint64_t)((addr & 0x3FFFF) >> 4) | ((uint64_t)(lbo >> 4) << 16) | ((uint64_t)(sbo >> 4) << 32) | ((uint64_t)swz << 62);
}
template <int BOFF, int SC>
__device__ __forceinline__ void wgmma_rs16(float* d, uint32_t a0, uint32_t a1, uint32_t a2, uint32_t a3, uint32_t blo) {
    asm volatile("{.reg .pred p; .reg .b32 l; .reg .b64 bd; setp.ne.b32 p, %14, 0; add.u32 l, %12, %13; mov.b64 bd, {l, 40};\n"
                 "wgmma.mma_async.sync.aligned.m64n16k16.f32.bf16.bf16 {%0,%1,%2,%3,%4,%5,%6,%7}, {%8,%9,%10,%11}, bd, p, 1, 1, 0;}"
                 : "+f"(d[0]), "+f"(d[1]), "+f"(d[2]), "+f"(d[3]), "+f"(d[4]), "+f"(d[5]), "+f"(d[6]), "+f"(d[7])
                 : "r"(a0), "r"(a1), "r"(a2), "r"(a3), "r"(blo), "n"(BOFF), "n"(SC));
}
template <int BOFF, int SC>
__device__ __forceinline__ void wgmma_rs32n(float* d, uint32_t a0, uint32_t a1, uint32_t a2, uint32_t a3, uint32_t blo) {
    asm volatile("{.reg .pred p; .reg .b32 l; .reg .b64 bd; setp.ne.b32 p, %22, 0; add.u32 l, %20, %21; mov.b64 bd, {l, 40};\n"
                 "wgmma.mma_async.sync.aligned.m64n32k16.f32.bf16.bf16 "
                 "{%0,%1,%2,%3,%4,%5,%6,%7,%8,%9,%10,%11,%12,%13,%14,%15}, {%16,%17,%18,%19}, bd, p, 1, 1, 0;}"
                 : "+f"(d[0]), "+f"(d[1]), "+f"(d[2]), "+f"(d[3]), "+f"(d[4]), "+f"(d[5]), "+f"(d[6]), "+f"(d[7]),
                   "+f"(d[8]), "+f"(d[9]), "+f"(d[10]), "+f"(d[11]), "+f"(d[12]), "+f"(d[13]), "+f"(d[14]), "+f"(d[15])
                 : "r"(a0), "r"(a1), "r"(a2), "r"(a3), "r"(blo), "n"(BOFF), "n"(SC));
}
template <int BOFF, int SC>
__device__ __forceinline__ void wgmma_rs32(float* d, uint32_t a0, uint32_t a1, uint32_t a2, uint32_t a3, uint32_t blo) {
    asm volatile("{.reg .pred p; .reg .b32 l; .reg .b64 bd; setp.ne.b32 p, %22, 0; add.u32 l, %20, %21; mov.b64 bd, {l, 0x40000040};\n"
                 "wgmma.mma_async.sync.aligned.m64n32k16.f32.bf16.bf16 "
                 "{%0,%1,%2,%3,%4,%5,%6,%7,%8,%9,%10,%11,%12,%13,%14,%15}, {%16,%17,%18,%19}, bd, p, 1, 1, 0;}"
                 : "+f"(d[0]), "+f"(d[1]), "+f"(d[2]), "+f"(d[3]), "+f"(d[4]), "+f"(d[5]), "+f"(d[6]), "+f"(d[7]),
                   "+f"(d[8]), "+f"(d[9]), "+f"(d[10]), "+f"(d[11]), "+f"(d[12]), "+f"(d[13]), "+f"(d[14]), "+f"(d[15])
                 : "r"(a0), "r"(a1), "r"(a2), "r"(a3), "r"(blo), "n"(BOFF), "n"(SC));
}
template <int AOFF, int BOFF, int SC>
__device__ __forceinline__ void wgmma_ss32(float* d, uint32_t alo, uint32_t blo) {
    asm volatile("{.reg .pred p; .reg .b32 l, m; .reg .b64 ad, bd; setp.ne.b32 p, %20, 0; add.u32 l, %16, %18; add.u32 m, %17, %19;\n"
                 "mov.b64 ad, {l, 0x40000040}; mov.b64 bd, {m, 0x40000040};\n"
                 "wgmma.mma_async.sync.aligned.m64n32k16.f32.bf16.bf16 "
                 "{%0,%1,%2,%3,%4,%5,%6,%7,%8,%9,%10,%11,%12,%13,%14,%15}, ad, bd, p, 1, 1, 1, 0;}"
                 : "+f"(d[0]), "+f"(d[1]), "+f"(d[2]), "+f"(d[3]), "+f"(d[4]), "+f"(d[5]), "+f"(d[6]), "+f"(d[7]),
                   "+f"(d[8]), "+f"(d[9]), "+f"(d[10]), "+f"(d[11]), "+f"(d[12]), "+f"(d[13]), "+f"(d[14]), "+f"(d[15])
                 : "r"(alo), "r"(blo), "n"(AOFF), "n"(BOFF), "n"(SC));
}
template <int AOFF, int BOFF, int SC>
__device__ __forceinline__ void wgmma_ss8(float* d, uint32_t alo, uint32_t blo) {
    asm volatile("{.reg .pred p; .reg .b32 l, m; .reg .b64 ad, bd; setp.ne.b32 p, %8, 0; add.u32 l, %4, %6; add.u32 m, %5, %7;\n"
                 "mov.b64 ad, {l, 0x40000040}; mov.b64 bd, {m, 0x8};\n"
                 "wgmma.mma_async.sync.aligned.m64n8k16.f32.bf16.bf16 {%0,%1,%2,%3}, ad, bd, p, 1, 1, 1, 1;}"
                 : "+f"(d[0]), "+f"(d[1]), "+f"(d[2]), "+f"(d[3]) : "r"(alo), "r"(blo), "n"(AOFF), "n"(BOFF), "n"(SC));
}
template <int OFF, int SC>
__device__ __forceinline__ void wgmma_ss40(float* d, uint32_t alo, uint32_t blo) {
    asm volatile("{.reg .pred p; .reg .b32 l, m; .reg .b64 ad, bd; setp.ne.b32 p, %23, 0; add.u32 l, %20, %22; add.u32 m, %21, %22;\n"
                 "mov.b64 ad, {l, 0x40000020}; mov.b64 bd, {m, 0x40000040};\n"
                 "wgmma.mma_async.sync.aligned.m64n40k16.f32.bf16.bf16 "
                 "{%0,%1,%2,%3,%4,%5,%6,%7,%8,%9,%10,%11,%12,%13,%14,%15,%16,%17,%18,%19}, ad, bd, p, 1, 1, 0, 0;}"
                 : "+f"(d[0]), "+f"(d[1]), "+f"(d[2]), "+f"(d[3]), "+f"(d[4]), "+f"(d[5]), "+f"(d[6]), "+f"(d[7]),
                   "+f"(d[8]), "+f"(d[9]), "+f"(d[10]), "+f"(d[11]), "+f"(d[12]), "+f"(d[13]), "+f"(d[14]), "+f"(d[15]),
                   "+f"(d[16]), "+f"(d[17]), "+f"(d[18]), "+f"(d[19])
                 : "r"(alo), "r"(blo), "n"(OFF), "n"(SC));
}
template <int I> using IC = std::integral_constant<int, I>;
template <int I, int N, class F> __device__ __forceinline__ void static_for(F&& f) {
    if constexpr (I < N) { f(std::integral_constant<int, I>{}); static_for<I + 1, N>(f); }
}
__device__ __forceinline__ uint32_t mapa(uint32_t a, uint32_t rank) {
    uint32_t r; asm("mapa.shared::cluster.u32 %0, %1, %2;" : "=r"(r) : "r"(a), "r"(rank)); return r;
}
__device__ __forceinline__ void st_async2(uint32_t a, uint32_t x, uint32_t y, uint32_t bar) {
    asm volatile("st.async.weak.shared::cluster.mbarrier::complete_tx::bytes.v2.b32 [%0], {%1,%2}, [%3];"
                 :: "r"(a), "r"(x), "r"(y), "r"(bar) : "memory");
}
__device__ __forceinline__ void st_async1(uint32_t a, uint32_t x, uint32_t bar) {
    asm volatile("st.async.weak.shared::cluster.mbarrier::complete_tx::bytes.b32 [%0], %1, [%2];" :: "r"(a), "r"(x), "r"(bar) : "memory");
}
__device__ __forceinline__ void st_async4(uint32_t a, uint32_t x, uint32_t y, uint32_t z, uint32_t w, uint32_t bar) {
    asm volatile("st.async.weak.shared::cluster.mbarrier::complete_tx::bytes.v4.b32 [%0], {%1,%2,%3,%4}, [%5];"
                 :: "r"(a), "r"(x), "r"(y), "r"(z), "r"(w), "r"(bar) : "memory");
}
__device__ __forceinline__ void sts2(uint32_t a, uint32_t x, uint32_t y) {
    asm volatile("st.shared.v2.b32 [%0], {%1,%2};" :: "r"(a), "r"(x), "r"(y) : "memory");
}
__device__ __forceinline__ void sts4(uint32_t a, uint4 v) {
    asm volatile("st.shared.v4.b32 [%0], {%1,%2,%3,%4};" :: "r"(a), "r"(v.x), "r"(v.y), "r"(v.z), "r"(v.w) : "memory");
}
__device__ __forceinline__ void sts1(uint32_t a, uint32_t x) { asm volatile("st.shared.b32 [%0], %1;" :: "r"(a), "r"(x) : "memory"); }
__device__ __forceinline__ float2 lds2f(uint32_t a) {
    float2 v; asm volatile("ld.shared.v2.f32 {%0,%1}, [%2];" : "=f"(v.x), "=f"(v.y) : "r"(a) : "memory"); return v;
}
__device__ __forceinline__ uint4 lds4(uint32_t a) {
    uint4 v; asm volatile("ld.shared.v4.b32 {%0,%1,%2,%3}, [%4];" : "=r"(v.x), "=r"(v.y), "=r"(v.z), "=r"(v.w) : "r"(a) : "memory"); return v;
}
__device__ __forceinline__ uint32_t lds1(uint32_t a) {
    uint32_t v; asm volatile("ld.shared.b32 %0, [%1];" : "=r"(v) : "r"(a) : "memory"); return v;
}
__device__ __forceinline__ void stg1(void* p, uint32_t x) { asm volatile("st.global.b32 [%0], %1;" :: "l"(p), "r"(x) : "memory"); }
__device__ __forceinline__ uint32_t ld_acquire(const uint32_t* p) {
    uint32_t v; asm volatile("ld.acquire.gpu.global.u32 %0, [%1];" : "=r"(v) : "l"(p) : "memory"); return v;
}
__device__ __forceinline__ uint32_t ld_relaxed(const void* p) {
    uint32_t v; asm volatile("ld.relaxed.gpu.global.u32 %0, [%1];" : "=r"(v) : "l"(p) : "memory"); return v;
}
__device__ __forceinline__ uint32_t ld_epoch() {
    uint32_t v; asm volatile("ld.relaxed.gpu.global.u32 %0, [%1];" : "=r"(v) : "l"(&g_epoch) : "memory"); return v + 1;
}
__device__ __forceinline__ void st_release(uint32_t* p, uint32_t v) { asm volatile("st.release.gpu.global.u32 [%0], %1;" :: "l"(p), "r"(v) : "memory"); }
__device__ __forceinline__ void st_pkt8(const void* p, uint32_t x, uint32_t y) {
    asm volatile("{.reg .b64 v; mov.b64 v, {%1,%2}; st.relaxed.gpu.global.b64 [%0], v;}" :: "l"(p), "r"(x), "r"(y) : "memory");
}
__device__ __forceinline__ void st_pkt4(const void* p, uint32_t x) {
    asm volatile("st.relaxed.gpu.global.b32 [%0], %1;" :: "l"(p), "r"(x) : "memory");
}
__device__ __forceinline__ uint4 ld_pkt(const void* p) {
    uint4 r;
    asm volatile("{.reg .b64 lo, hi; .reg .b128 v; ld.relaxed.gpu.global.b128 v, [%4]; mov.b128 {lo, hi}, v;\n"
                 "mov.b64 {%0,%1}, lo; mov.b64 {%2,%3}, hi;}"
                 : "=r"(r.x), "=r"(r.y), "=r"(r.z), "=r"(r.w) : "l"(p) : "memory");
    return r;
}

template <int OFF> __device__ __forceinline__ void ld_pkt_stale(uint4& r, const void* p, uint32_t tag) {
    asm volatile("{.reg .pred p; .reg .b32 t; .reg .b64 lo, hi; .reg .b128 v; lop3.b32 t, %0, %5, 1, 0x28; setp.ne.u32 p, t, 0;\n"
                 "mov.b64 lo, {%0,%1}; mov.b64 hi, {%2,%3}; mov.b128 v, {lo, hi}; @p ld.relaxed.gpu.global.b128 v, [%4 + %6];\n"
                 "mov.b128 {lo, hi}, v; mov.b64 {%0,%1}, lo; mov.b64 {%2,%3}, hi;}"
                 : "+r"(r.x), "+r"(r.y), "+r"(r.z), "+r"(r.w) : "l"(p), "r"(tag), "n"(OFF) : "memory");
}

constexpr int NX = 7;
constexpr uint32_t OFF_WV = 0, OFF_WO = 81920, OFF_XR = OFF_WO + 86016, OFF_QA = OFF_XR + NX * 4096, OFF_SP = OFF_QA + 5120, OFF_RED = OFF_SP,
                   OFF_BAR = OFF_SP + 2560, OFF_KA = OFF_QA + 8192, OFF_MEMT = OFF_KA + 5120, OFF_SM = OFF_MEMT + 10240, OFF_PM = OFF_SM + 1280,
                   OFF_SX = OFF_PM + 768, OFF_R1 = OFF_SX + 5120, OFF_OX = OFF_R1, OFF_DBG = OFF_R1 + 4096, CHAIN_SMEM = OFF_DBG + 1024,
                   OFF_OXL = OFF_XR, OFF_OXG = OFF_XR + 4096, OFF_R1L = OFF_XR + 20480, OFF_TRED = OFF_WV + 32768;
__host__ __device__ constexpr uint32_t xblk(int kb) { return kb < 3 ? OFF_MEMT - OFF_XR + kb * 4096 : (kb - 3) * 4096; }
constexpr uint32_t MB_S = OFF_BAR, MB_SX = OFF_BAR + 8, MB_O = OFF_BAR + 16, MB_WO = OFF_BAR + 24, MB_XA = OFF_BAR + 32, MB_XB = OFF_BAR + 40,
                   MB_M = OFF_BAR + 48, MB_EM = OFF_BAR + 88, MB_EA = OFF_BAR + 96, OFF_EP = OFF_BAR + 112,
                   MB_F = OFF_BAR + 128, MB_E = OFF_BAR + 168, OFF_ROLE = OFF_BAR + 224, OFF_T = OFF_BAR + 232, OFF_SPO = OFF_BAR + 236, MB_M2 = OFF_BAR + 240;
constexpr int BAR_QM = 0, BAR_PUB = 1, BAR_QK = 2, BAR_P = 3, BAR_WO = 4, BAR_S = 5, BAR_O2 = 6, BAR_O = 7, BAR_R = 8, BAR_PM = 9, BAR_G = 10,
              BAR_X = 15, BAR_R1 = 15, BAR_MEM = 11;
constexpr float SCL_B = 0.07216878364870322f * 1.4426950408889634f;
#define NPROBE 3
#define G1 1056
#define G2 1536
#define F1 0
#define F2 4
#define BN 8
#define BD 1
#define NVR 4
#define NVP 6
#define NVE 6
#define NPF 12
#define NPE 1
#define NPM 7
#define PFV 1
#define PROG 0x5111010101010100ull
#define LEAD 4
#define NV0 3
#define HV 3
#define REL 2
#define RB 1
#define TXD 0
#define TXE 0
#define WOK 0x888
#define AJ 2
#define KJ 9
#define XG 1
#define VFLAGS 0x101010101010444ull
#define SD 0
#define NO2 6
#define OE 0
#define DN 17
#define NOB 2
#define PW0 7
#define PW1 4
#define NVC 2
#define PWIN 2
#define NCP 1

static_assert(PWIN <= 2, "the third piece of the weights is requested behind the store of the epoch, which orders its first use");
static_assert((VFLAGS & ((4ull << NVC) - 1)) == 1ull << NVC, "first block of v");
__device__ __forceinline__ uint32_t clk32() { uint32_t c; asm volatile("mov.u32 %0, %%clock;" : "=r"(c)); return c; }
__device__ __forceinline__ void spin(uint32_t n) { const uint32_t t = clk32(); while (clk32() - t < n) { } }
__device__ __forceinline__ uint32_t gtime() { uint32_t c; asm volatile("mov.u32 %0, %%globaltimer_lo;" : "=r"(c)); return c; }
__device__ __forceinline__ void ggate(uint32_t t) { while ((int)(gtime() - t) < 0) { } }
template <int N> __device__ __forceinline__ void pause() {
    if constexpr (N > 0) {
        uint32_t x = clk32();
#pragma unroll
        for (int i = 1; i < N; i++) asm volatile("mad.lo.u32 %0, %0, %0, %0;" : "+r"(x));
        asm volatile("{.reg .pred p; .reg .b32 t; mad.lo.u32 t, %0, %0, %0; setp.eq.u32 p, t, 1; @p exit;}" :: "r"(x) : "memory");
    }
}
__device__ __forceinline__ uint32_t laneid() { uint32_t c; asm volatile("mov.u32 %0, %%laneid;" : "=r"(c)); return c; }
template <int K> __device__ __forceinline__ uint32_t opq0(uint32_t s) { uint32_t c; asm volatile("shr.u32 %0, %1, %2;" : "=r"(c) : "r"(s), "n"(K)); return c; }
__device__ __forceinline__ uint32_t keep(uint32_t x) { asm volatile("" : "+r"(x)); return x; }
template <class T> __device__ __forceinline__ T* keepp(T* p) { asm volatile("" : "+l"(p)); return p; }
__device__ __forceinline__ void sched() { asm volatile("bar.warp.sync 0xffffffff;" ::: "memory"); }
__device__ __forceinline__ void blk(int s) { asm volatile("{.reg .pred p; setp.gt.s32 p, %0, 1000; @p exit;}" :: "r"(s) : "memory"); }
__device__ __forceinline__ uint32_t selu(bool c, uint32_t a, uint32_t b) {
    uint32_t r; asm("{.reg .pred p; setp.ne.u32 p, %1, 0; selp.b32 %0, %2, %3, p;}" : "=r"(r) : "r"((uint32_t)c), "r"(a), "r"(b)); return r;
}
__device__ __forceinline__ float bf_lo(uint32_t w) { return __uint_as_float(w << 16); }
__device__ __forceinline__ float bf_hi(uint32_t w) { return __uint_as_float(w & 0xffff0000u); }
__device__ __forceinline__ uint32_t badd2(uint32_t a, uint32_t b) { uint32_t r; asm("add.rn.bf16x2 %0, %1, %2;" : "=r"(r) : "r"(a), "r"(b)); return r; }
__device__ __forceinline__ uint32_t tagx(uint32_t a, uint32_t b, uint32_t t) { uint32_t r; asm("lop3.b32 %0, %1, %2, %3, 0x7e;" : "=r"(r) : "r"(a), "r"(t), "r"(b)); return r; }
__device__ __forceinline__ uint32_t tagv(uint32_t a, uint32_t b, uint32_t t) { uint32_t r; asm volatile("lop3.b32 %0, %1, %2, %3, 0x7e;" : "=r"(r) : "r"(a), "r"(t), "r"(b)); return r; }
__device__ __forceinline__ uint32_t or3(uint32_t a, uint32_t b, uint32_t c) { uint32_t r; asm("lop3.b32 %0, %1, %2, %3, 0xfe;" : "=r"(r) : "r"(a), "r"(b), "r"(c)); return r; }
__device__ __forceinline__ bool any_bit0(uint32_t a, uint32_t b) {
    uint32_t r;
    asm volatile("{.reg .pred p; .reg .b32 t; lop3.b32 t, %1, 1, %2, 0xc8; setp.ne.u32 p, t, 0; vote.sync.any.pred p, p, 0xffffffff; selp.u32 %0, 1, 0, p;}"
                 : "=r"(r) : "r"(a), "r"(b));
    return r;
}
__device__ __forceinline__ void arrive_e(uint32_t bar) {
    asm volatile("{.reg .pred p; elect.sync _|p, 0xffffffff; @p mbarrier.arrive.shared::cta.b64 _, [%0];}" :: "r"(bar) : "memory");
}
__device__ __forceinline__ void expect_e(uint32_t bar, uint32_t bytes) {
    asm volatile("{.reg .pred p; elect.sync _|p, 0xffffffff; @p mbarrier.arrive.expect_tx.shared::cta.b64 _, [%0], %1;}" :: "r"(bar), "r"(bytes) : "memory");
}
__device__ __forceinline__ void tma2d_e(uint32_t dst, const CUtensorMap* tm, int c0, int c1, uint32_t bar) {
    asm volatile("{.reg .pred p; elect.sync _|p, 0xffffffff;\n"
                 "@p cp.async.bulk.tensor.2d.shared::cluster.global.mbarrier::complete_tx::bytes [%0], [%1, {%3, %4}], [%2];}"
                 :: "r"(dst), "l"(tm), "r"(bar), "r"(c0), "r"(c1) : "memory");
}
__device__ __forceinline__ void ldsm4_if(bool c, uint32_t a, uint32_t& r0, uint32_t& r1, uint32_t& r2, uint32_t& r3) {
    asm volatile("{.reg .pred p; setp.ne.u32 p, %5, 0; @p ldmatrix.sync.aligned.m8n8.x4.shared.b16 {%0,%1,%2,%3}, [%4];}"
                 : "+r"(r0), "+r"(r1), "+r"(r2), "+r"(r3) : "r"(a), "r"((uint32_t)c) : "memory");
}
__device__ __forceinline__ bool arrive_unless(uint32_t a, uint32_t m, int bar, int n) {
    uint32_t r;
    asm volatile("{.reg .pred p; .reg .b32 t; and.b32 t, %1, %2; setp.ne.u32 p, t, 0; vote.sync.any.pred p, p, 0xffffffff; @!p bar.arrive %3, %4;"
                 " selp.u32 %0, 1, 0, p;}" : "=r"(r) : "r"(a), "r"(m), "r"(bar), "r"(n) : "memory");
    return r;
}
__device__ __forceinline__ bool sync_unless(uint32_t a, uint32_t b, uint32_t m, int bar, int n) {
    uint32_t r;
    asm volatile("{.reg .pred p; .reg .b32 t; lop3.b32 t, %1, %2, %3, 0xa8; setp.ne.u32 p, t, 0; vote.sync.any.pred p, p, 0xffffffff; @!p bar.sync %4, %5;"
                 " selp.u32 %0, 1, 0, p;}" : "=r"(r) : "r"(a), "r"(b), "r"(m), "n"(BAR_R), "n"(128) : "memory");
    return r;
}
__device__ __forceinline__ uint32_t pack2v(float lo, float hi) {
    uint32_t r; asm volatile("cvt.rn.bf16x2.f32 %0, %1, %2;" : "=r"(r) : "f"(hi), "f"(lo)); return r;
}
__device__ __forceinline__ void st_pkt(const void* p, uint4 v) {
    asm volatile("{.reg .b64 lo, hi; .reg .b128 v; mov.b64 lo, {%1,%2}; mov.b64 hi, {%3,%4}; mov.b128 v, {lo, hi}; st.relaxed.gpu.global.b128 [%0], v;}"
                 :: "l"(p), "r"(v.x), "r"(v.y), "r"(v.z), "r"(v.w) : "memory");
}
__device__ __forceinline__ void bulk_ld_e(uint32_t dst, const void* src, uint32_t bytes, uint32_t bar) {
    asm volatile("{.reg .pred p; elect.sync _|p, 0xffffffff;\n"
                 "@p cp.async.bulk.shared::cluster.global.mbarrier::complete_tx::bytes [%0], [%1], %2, [%3];}"
                 :: "r"(dst), "l"(src), "r"(bytes), "r"(bar) : "memory");
}
template <int OFF> __device__ __forceinline__ void ld_pkt8(uint32_t& x, uint32_t& y, const void* p) {
    asm volatile("{.reg .b64 v; ld.relaxed.gpu.global.b64 v, [%2 + %3]; mov.b64 {%0,%1}, v;}" : "=r"(x), "=r"(y) : "l"(p), "n"(OFF) : "memory");
}
__device__ __forceinline__ void tma3d_e(uint32_t dst, const CUtensorMap* tm, int c1, int c2, uint32_t bar) {
    asm volatile("{.reg .pred p; elect.sync _|p, 0xffffffff;\n"
                 "@p cp.async.bulk.tensor.3d.shared::cluster.global.mbarrier::complete_tx::bytes [%0], [%1, {0, %3, %4}], [%2];}"
                 :: "r"(dst), "l"(tm), "r"(bar), "r"(c1), "r"(c2) : "memory");
}

constexpr uint32_t XCH_PART = 0x80000;
__device__ __forceinline__ uint32_t xch_line(uint32_t r) { return r ^ ((1 ^ r >> 1 ^ r >> 4 ^ r >> 5) & 1); }
__host__ __device__ constexpr uint32_t xch_mem(uint32_t cg) { return 0x48000 + (cg & 1) * 0x4000 + (cg >> 1) * 0x100000; }
__host__ __device__ constexpr uint32_t xch_copy(uint32_t k) { return (0x22123000u >> 8 * k & 255) << 12; }
__device__ __forceinline__ uint32_t mem_row(uint32_t c) { return (c & 16) * 16 + (c & 4) * 32 + ((((c >> 1) ^ c) & 4) | (c & 3)) * 16; }

#define BORD 0xcb43a29180ull
__host__ __device__ constexpr int bulk_ord(int h) { return (BORD >> 4 * h) & 15; }
__host__ __device__ constexpr int bulk_pos(int k) {
    int r = -1;
    for (int h = 0; h < 10; h++) {
        const int v = bulk_ord(h);
        if ((k == 0 ? (v & 7) == 2 : k == 3 ? (v & 7) < 3 : (v >> 3) == (k == 2)) && (k >= 3 || r < 0)) r = h;
    }
    return r;
}

__device__ __forceinline__ void set_role(uint32_t sb, uint32_t r) {
    const uint32_t role = xch_line(r);
    sts1(sb + OFF_ROLE, role | (xch_mem((role & 255) / 20) + ((role & 255) % 20) * 128) << 2);
    sts1(sb + OFF_SPO, 0x44000 + xch_copy(1 + (role >> 1 & 1)) + (role >> 8) * 4096);
}
__device__ __forceinline__ void pick_role(uint32_t sb, bool second, uint32_t page, const char* pp, uint32_t ep) {
    uint32_t* const g_near = reinterpret_cast<uint32_t*>(g_near4);
    const uint32_t ln = laneid();
    if (!second) {
        if (ln == 0) {
            uint32_t t = 4095;
#pragma unroll 1
            for (int i = 0; i < NPROBE; i++) {
                const uint32_t c0 = clk32();
                uint32_t c1 = c0 - 1;
                asm volatile("{.reg .pred p; .reg .b32 x; atom.relaxed.gpu.global.exch.b32 x, [%1], %2; setp.le.u32 p, x, %2; @p mov.u32 %0, %%clock;}"
                             : "+r"(c1) : "l"(pp + page * 4096), "r"(i) : "memory");
                t = min(t, c1 - c0);
            }
            asm volatile("st.relaxed.gpu.global.v4.b32 [%0], {%1,%1,%1,%1}; st.relaxed.gpu.global.v4.b32 [%0 + 16], {%1,%1,%1,%1};"
                         :: "l"(g_near + blockIdx.x * 16 + page * 8), "r"(ep << 12 | t) : "memory");
        }
        __syncwarp();
    } else {
        int d = 0;
#pragma unroll 1
        for (int c = 0; c < SPIN_LIM; c++) {
            uint32_t bad = 0;
            d = 0;
#pragma unroll
            for (int i = 0; i < 6; i++) { const uint32_t a = ld_relaxed(g_near + ln * 48 + i * 8); bad |= a ^ ep << 12; d += i & 1 ? -(int)a : (int)a; }
            if (__all_sync(0xffffffffu, bad < 4096)) break;
            __nanosleep(100);
        }
        const uint32_t bm = __ballot_sync(0xffffffffu, d > 0), cl = blockIdx.x / 3;
        const uint32_t side = bm >> cl & 1;
        const int n1 = 3 * __popc(bm), r1 = 3 * __popc(bm & ((1u << cl) - 1));
        const int rk = side ? r1 + blockIdx.x % 3 : blockIdx.x - r1, no = side ? 96 - n1 : n1;
        const uint32_t next = side << 8 | (rk < 40 ? 2 * rk + side : min(2 * (no + rk - 40) + (side ^ 1), 95));
        set_role(sb, next);
    }
}

__host__ __device__ constexpr int out_ord(int n) {
    return n < 8 ? n : n < 8 + LEAD ? 2 * (n - 4) : n >= 24 - LEAD ? 2 * (n - 12) + 1 : (n - LEAD) & 1 ? n - LEAD : n + LEAD;
}
__device__ __forceinline__ void share_o(uint32_t sb, uint32_t rank, uint32_t src, uint32_t t) {
#pragma unroll
    for (uint32_t p = 1; p < 3; p++) {
        const uint32_t pb = mapa(sb, (rank + p) % 3);
        asm volatile("{.reg .pred p; elect.sync _|p, 0xffffffff;\n"
                     "@p cp.async.bulk.shared::cluster.shared::cta.mbarrier::complete_tx::bytes [%0], [%1], 4096, [%2];}"
                     :: "r"(pb + OFF_OXG + t * 8192 + (2 - p) * 4096), "r"(sb + src), "r"(pb + MB_F + 8 * t) : "memory");
    }
}

#define LANE_REGS const uint32_t l16 = __shfl_sync(0xffffffffu, sb + (tid & 31) * 16, tid & 31); const int lane = (l16 - sb) >> 4

__global__ void __cluster_dims__(3, 1, 1) __launch_bounds__(384, 1)
chain_kernel(const __grid_constant__ CUtensorMap tmXA, const __grid_constant__ CUtensorMap tmXB, const __grid_constant__ CUtensorMap tmWq, const __grid_constant__ CUtensorMap tmWk,
             const __grid_constant__ CUtensorMap tmWv, const __grid_constant__ CUtensorMap tmWo,
             const __grid_constant__ CUtensorMap tmOx, const bf16* __restrict__ mem0,
             const char* win,
             bf16* out)
{
    extern __shared__ __align__(1024) uint8_t smem[];
    const uint32_t sb = smem_u32(smem);
    const int tid = threadIdx.x;
    const int warp = __shfl_sync(0xffffffffu, tid >> 5, 0);
    uint32_t rank; asm("mov.u32 %0, %%cluster_ctarank;" : "=r"(rank));
    const int head = blockIdx.x / 3;
    if (tid == 256) {
#pragma unroll
        for (int i = 0; i < PWIN; i++) mbar_init(sb + MB_F + 8 * i, 1);
        asm volatile("fence.proxy.async.shared::cta;" ::: "memory");
#pragma unroll
        for (int i = 0; i < PWIN; i++) {
            tma2d(sb + OFF_WV + i * 16384, &tmWq, blockIdx.x * 64, i * 128, sb + MB_F + 8 * i);
            tma2d(sb + OFF_WO + i * 16384, &tmWk, blockIdx.x * 64, i * 128, sb + MB_F + 8 * i);
            mbar_expect(sb + MB_F + 8 * i, 32768);
        }
    }
    if (tid == 288) {
        mbar_init(sb + MB_XA, 2); mbar_init(sb + MB_XB, 1);
        mbar_init(sb + MB_S, 5); mbar_init(sb + MB_SX, 1); mbar_init(sb + MB_O, 1); mbar_init(sb + MB_WO, 1);
        for (int i = 0; i < 4; i++) { mbar_init(sb + MB_M + 8 * i, 1); mbar_init(sb + MB_M2 + 8 * i, 1); }
        mbar_init(sb + MB_EM, 4); mbar_init(sb + MB_EA, 8);
        for (int i = 0; i < 5; i++) { if (i >= PWIN) mbar_init(sb + MB_F + 8 * i, 1); mbar_init(sb + MB_E + 8 * i, 8); }
        asm volatile("fence.mbarrier_init.release.cluster;" ::: "memory");
        asm volatile("fence.proxy.async.shared::cta;" ::: "memory");
        mbar_expect(sb + MB_XA, NX * 4096); mbar_expect(sb + MB_XA, 8192); mbar_expect(sb + MB_XB, 4096);
        for (int i = 0; i < 4; i++)
                asm volatile("cp.async.bulk.tensor.3d.shared::cluster.global.mbarrier::complete_tx::bytes [%0], [%1, {0, 0, %3}], [%2];"
                             :: "r"(sb + OFF_XR + xblk(i)), "l"(i == 3 ? &tmXA : &tmXB), "r"(sb + (i == 2 ? MB_XB : MB_XA)), "r"(i) : "memory");
        mbar_expect(sb + MB_WO, 86016);
    }
    __syncwarp();
    const char* pp = win + 0x44000 + (blockIdx.x & 63) * 64 + (blockIdx.x >> 6) * 0x100000;
    if (warp >= 10 && (tid & 31) < 8) st_pkt4(pp + (warp & 1) * 4096 + (tid & 7) * 4, 0);
    const uint32_t ep0 = ld_relaxed(&g_epoch);
    if (tid >= 160 && tid < 240) asm volatile("prefetch.global.L2 [%0];" :: "l"(mem0 + (tid - 160) * 64));
    if (tid >= 64 && tid < 67) asm volatile("prefetch.tensormap [%0];" :: "l"(tid == 64 ? &tmWv : tid == 65 ? &tmWo : &tmOx) : "memory");
    asm volatile("griddepcontrol.launch_dependents;" ::: "memory");
    __syncthreads();
    asm volatile("barrier.cluster.arrive.release.aligned;" ::: "memory");

    if (warp < 8) {
        asm volatile("setmaxnreg.inc.sync.aligned.u32 224;");
        LANE_REGS;
        const int w4 = warp & 3;
        const uint32_t st0 = __shfl_sync(0xffffffffu, sb + (warp >> 2) * 8192 + ((lane & 7) + ((lane >> 4) << 3)) * 128 +
                                                      (((2 * w4 + ((lane >> 3) & 1)) ^ (lane & 7)) << 4), lane);
        const uint32_t st_addr = st0 + OFF_QA;
        const uint32_t xr_lo = (((sb + OFF_XR) & 0x3FFFF) >> 4) | (1u << 16);
        const uint32_t p1 = mapa(sb, (rank + 1) % 3), p2 = mapa(sb, (rank + 2) % 3), p1s = p1 - sb + OFF_SP, p2s = p2 - sb + OFF_SP + 1280;
        const uint32_t box = rank * 7 + warp;
        const bool act = warp < 7 && box < 20;
        const uint32_t gp = XCH_PART + box * 0x4000 + head * 128;
        const int wg = __reduce_max_sync(0xffffffffu, (unsigned)tid >> 7);
        const uint32_t vo = __reduce_max_sync(0xffffffffu, ((unsigned)tid >> 7) * 32768);
        const uint32_t mo = __reduce_max_sync(0xffffffffu, ((unsigned)tid >> 7) * 5120);
        const uint32_t xa_lo = xr_lo + wg * 5 * 256, xb_lo = xr_lo + xblk(0) / 16 + wg * (2 * 256 - xblk(0) / 16);
        uint32_t wa[80], wb[80];
        {
            const uint32_t src = st_addr - OFF_QA + wg * (40960 - 8192);
            if (wg) { arrive_e(sb + MB_E); arrive_e(sb + MB_E + 8); } else { arrive_e(sb + MB_E + 24); arrive_e(sb + MB_E + 32); }
#pragma unroll
            for (int k = 0; k < 20; k++) {
                if (k % 4 == 0) mbar_wait(sb + MB_F + ((wg * 20 + k) >> 3) * 8, 0);
                ldsm4t(src + wg * OFF_WO + k * 2048, wa[4 * k], wa[4 * k + 1], wa[4 * k + 2], wa[4 * k + 3]);
                ldsm4t(src + (wg ^ 1) * OFF_WO + k * 2048, wb[4 * k], wb[4 * k + 1], wb[4 * k + 2], wb[4 * k + 3]);
                if (k % 4 == 3 && (k == 19 || (k & 4) >> 2 != wg)) arrive_e(sb + MB_E + ((wg * 20 + k) >> 3) * 8);
            }
        }
        asm volatile("barrier.cluster.wait.acquire.aligned;" ::: "memory");
        mbar_wait(sb + MB_XA, 0);
        const uint32_t lb = __shfl_sync(0xffffffffu, sb + mem_row(tid & 31), tid & 31);

        for (int s = 0; ; s++) {
            uint32_t b[10][4], v[20][4];
            auto ldv = [&](int n) { ldsm4t(st0 + vo + (OFF_WV + n * 2048), v[n][0], v[n][1], v[n][2], v[n][3]); };
            auto ldb = [&](int j) { ldsm4t(lb + mo + (OFF_MEMT + j * 512), b[j][0], b[j][1], b[j][2], b[j][3]); };
#pragma unroll
            for (int n = 0; n < NV0; n++) ldv(n);
            if (s > 0) bar_sync(BAR_WO, 384);
            {
                float pa[16], acc[16];
#pragma unroll
                for (int i = 0; i < 16; i++) pa[i] = acc[i] = 0.f;
                static_for<0, 10>([&](auto H) {
                    constexpr int h = H.value, kb = bulk_ord(h) & 7, own = bulk_ord(h) >> 3;
                    if constexpr (h == bulk_pos(0)) { if (!wg) mbar_wait(sb + MB_XB, s & 1); }
                    if constexpr (h == PW0 && h == bulk_pos(3) + 1) { if (!wg) { wg_wait<0>(); arrive_e(sb + MB_EM); } }
                    if constexpr (h == PW0 || h == PW1) { if (s >= NVC && (PW0 == PW1 || (h == PW0 ? !wg : wg))) { bar_sync(BAR_PUB, 288); } }
                    if (h == 0 || h == bulk_pos(3) + 1 + (PW0 != bulk_pos(3) + 1) || h == bulk_pos(4) + 2 || h == bulk_pos(0)) wg_fence();
                    static_for<0, 4>([&](auto K4) {
                        constexpr int k4 = K4.value, r = 16 * kb + 4 * k4;
                        const uint32_t* w = own ? wa : wb;
                        wgmma_rs32<(kb < 3 ? kb : kb - 3) * 256 + k4 * 2, k4 != 0 || h != bulk_pos(1 + own)>(own ? acc : pa, w[r], w[r + 1], w[r + 2], w[r + 3], kb < 3 ? xb_lo : xa_lo);
                    });
                    wg_commit();
                    if constexpr (h == HV) {
#pragma unroll
                        for (int n = NV0; n < NVE; n++) ldv(n);
                    }
                    if constexpr (h != PW0 && h == bulk_pos(3) + 1) { if (!wg) { wg_wait<1>(); arrive_e(sb + MB_EM); } }
                    if constexpr (h == bulk_pos(4) + 1) {
                        const uint32_t st_oth = keep((((st0 ^ opq0<8>(s)) - sb) ^ 8192) + sb) + OFF_QA;
                        wg_wait<1>();
                        stsm4t(st_oth + 1024, pack2(pa[0], pa[1]), pack2(pa[2], pa[3]), pack2(pa[4], pa[5]), pack2(pa[6], pa[7]));
                        stsm4t(st_oth + 3072, pack2(pa[8], pa[9]), pack2(pa[10], pa[11]), pack2(pa[12], pa[13]), pack2(pa[14], pa[15]));
                    }
                });
                if (s == 0) {
                    if (warp == 2) pick_role(sb, true, 0, pp, lds1(sb + OFF_EP));
#pragma unroll 1
                    for (int i = warp >> 1 & 2; i < (warp >> 1 & 2) + 3; i++) { mbar_wait_long(sb + MB_E + 8 * i, 0); mbar_wait_long(sb + MB_F + 8 * i, 1); }
#pragma unroll
                    for (int n = 0; n < NVE; n++) ldv(n);
                }
                bar_sync(BAR_QK, 256);
                uint32_t u[8];
                ldsm4t(st_addr + 1024, u[0], u[1], u[2], u[3]);
                ldsm4t(st_addr + 3072, u[4], u[5], u[6], u[7]);
#pragma unroll
                for (int n = NVE; n < NVP; n++) ldv(n);
                wg_wait<0>();
                arrive_e(sb + MB_EA);
#pragma unroll
                for (int i = 0; i < 8; i++) u[i] = badd2(u[i], pack2(acc[2 * i], acc[2 * i + 1]));
                stsm4t(st_addr + 1024, u[0], u[1], u[2], u[3]);
                stsm4t(st_addr + 3072, u[4], u[5], u[6], u[7]);
                if (RB && wg) bar_arrive(BAR_R1, 288);
            }
            uint32_t lo = 0, so = 0, a[16], kb[8], k1[8];
            const uint32_t r1 = s == NSEG - 1 ? OFF_R1L : OFF_R1;
            float cv[4] = {0, 0, 0, 0};
            {
                float ca[4] = {0, 0, 0, 0}, cb[4] = {0, 0, 0, 0};
                uint32_t sq = 0, ln = 0, lq = 0, lk = 0;
                blk(warp);
                if (wg) bar_sync(BAR_MEM + 2, 160); else bar_sync(BAR_MEM, 160);
                int nb = 0, nv = NVP;
                for (; nb < BD; nb++) ldb(nb);
#pragma unroll
                for (int j = 0; j < 10; j++) {
                    if (2 * j == BN) { if (wg) bar_sync(BAR_MEM + 3, 160); else bar_sync(BAR_MEM + 1, 160); }
                    for (; nb <= j + BD && nb < (2 * j >= BN ? 10 : 5); nb++) ldb(nb);
                    if (j == KJ) {
                        if (!RB) bar_sync(BAR_R1, 288); else if (wg) bar_sync(BAR_PM, 160); else bar_sync(BAR_R1, 288);
#pragma unroll
                        for (int i = 0; i < 4; i++) { kb[i] = b[KJ - 2][i]; kb[4 + i] = b[KJ - 1][i]; }
                        ldsm4_if((uint32_t)(warp - 1) < 4, OFF_KA + lo, kb[0], kb[1], kb[2], kb[3]);
                        ldsm4_if((uint32_t)(warp - 1) < 4, OFF_KA + (lo ^ 64), kb[4], kb[5], kb[6], kb[7]);
                    }
                    blk(warp);
#pragma unroll
                    for (int i = 0; i < 2; i++) {
                        const int n = 2 * j + i;
                        if (i && n == BN) {
                            if (wg) bar_sync(BAR_MEM + 3, 160); else bar_sync(BAR_MEM + 1, 160);
                            for (; nb <= j + BD; nb++) ldb(nb);
                            blk(warp);
                        }
                        mma16(cb, wb[4 * n], wb[4 * n + 1], wb[4 * n + 2], wb[4 * n + 3], b[j][2 * i], b[j][2 * i + 1]);
                        mma16(ca, wa[4 * n], wa[4 * n + 1], wa[4 * n + 2], wa[4 * n + 3], b[j][2 * i], b[j][2 * i + 1]);
                        mma16(cv, v[n][0], v[n][1], v[n][2], v[n][3], b[j][2 * i], b[j][2 * i + 1]);
                        if (n >= NVP - NVR && nv < 20) ldv(nv++);
                    }
                    if (j == AJ) { const uint32_t o = (st0 ^ opq0<9>(s)) - sb; ln = keep((o >> 7 & 7) | ((o ^ o >> 3) >> 1 & 8) | (o >> 6 & 16)); }
                    if (j == AJ + 1) lo = keep(sb + (ln & 7) * 128 + (((ln >> 3) ^ (ln & 7)) << 4) + warp * 1024);
                    if (j == AJ + 2) {
                        lk = keep(sb + ln * 16);
                        sq = keep((lk & ~256u) + (warp & 3) * 256 + selu((ln >> 4) == warp >> 2, r1 + (warp >> 2) * 1024, OFF_KA - (warp >> 2) * 8192));
                    }
                    if (j == AJ + 3) so = keep(sb + warp * 256 + ((ln * 8) ^ (warp & 3) * 32));
                    if (j == AJ + 4) lq = keep(sb + r1 + (ln & 8) * 128 + (ln >> 4) * 128 + (ln & 7) * 16);
                    if (j == AJ + 5) {
#pragma unroll
                        for (int i = 0; i < 8; i++) k1[i] = opq0<11>(s);
                    }
                }
                a[0] = pack2(ca[0], ca[1]); a[1] = pack2(ca[2], ca[3]); a[2] = pack2(cb[0], cb[1]); a[3] = pack2(cb[2], cb[3]);
                stsm4t(sq, a[0], a[1], a[2], a[3]);
                sts2(so + r1 + 2048, pack2(cv[0], cv[1]), pack2(cv[2], cv[3]));
                bar_sync(BAR_QM, 256);
#pragma unroll
                for (int i = 0; i < 4; i++) { a[4 + i] = __float_as_uint(ca[i]); a[8 + i] = __float_as_uint(cb[i]); a[12 + i] = b[9][i]; }
                ldsm4_if(warp < 5, lq, a[0], a[1], a[2], a[3]);
                ldsm4_if(warp == 0, lk + OFF_KA, kb[0], kb[1], kb[2], kb[3]);
                ldsm4_if(warp < 5, lq + 256, a[4], a[5], a[6], a[7]);
                ldsm4_if(warp == 0, lk + OFF_QA, k1[0], k1[1], k1[2], k1[3]);
                ldsm4_if(warp < 5, lq + 512, a[8], a[9], a[10], a[11]);
                ldsm4_if(warp == 0, lk + OFF_KA + 512, kb[4], kb[5], kb[6], kb[7]);
                ldsm4_if(warp < 5, lq + 768, a[12], a[13], a[14], a[15]);
                ldsm4_if(warp == 0, lk + OFF_QA + 512, k1[4], k1[5], k1[6], k1[7]);
            }
            if (__builtin_expect(warp < 5, 1)) {
                const uint32_t r1a = keep(p1s + so), r2a = keep(p2s + so), m1 = keep(p1 + MB_S), m2 = keep(p2 + MB_S);
                blk(warp);
#pragma unroll
                for (int i = 0; i < 8; i++) kb[i] = badd2(kb[i], k1[i]);
                float d[4][4];
#pragma unroll
                for (int i = 0; i < 4; i++) {
                    d[i][0] = d[i][1] = d[i][2] = d[i][3] = 0.f;
                    mma16(d[i], a[4 * i], a[4 * i + 1], a[4 * i + 2], a[4 * i + 3], kb[2 * i], kb[2 * i + 1]);
                }
                const uint32_t x = __float_as_uint((((d[0][0] + d[0][2]) + (d[1][0] + d[1][2])) + (d[2][0] + d[2][2])) + (d[3][0] + d[3][2]));
                const uint32_t y = __float_as_uint((((d[0][1] + d[0][3]) + (d[1][1] + d[1][3])) + (d[2][1] + d[2][3])) + (d[3][1] + d[3][3]));
                st_async2(r1a, x, y, m1);
                st_async2(r2a, x, y, m2);
                sts2(so + OFF_SM, x, y);
                __syncwarp();
                expect_e(sb + MB_S, 512);
                if (warp == 0) { stsm4(OFF_KA + lo, kb[0], kb[1], kb[2], kb[3]); stsm4(OFF_KA + (lo ^ 64), kb[4], kb[5], kb[6], kb[7]); }
                bar_arrive(BAR_S, 288); bar_arrive(BAR_O2, 256);
            } else {
                if (warp == 7 && s < NSEG - 1) {
                    pause<SD>();
                    const uint32_t now = gtime() & ~31u, ln = laneid(), sq = (s - lds1(sb + OFF_EP)) & 3;
                    if (ln < 4) st_pkt4(win + 0x44000 + xch_copy(1 + (ln & 1)) + (ln >> 1) * 4096 + blockIdx.x * 4, now | sq);
                    __syncwarp();
                }
                if (warp == 6 && s < NSEG - 1) {
                    asm volatile("fence.proxy.async.shared::cta;" ::: "memory");
                    expect_e(sb + MB_XA, 8192);
                    tma3d_e(sb + OFF_MEMT, &tmXB, (s + 1) * 32, 0, sb + MB_XA);
                    tma3d_e(sb + OFF_MEMT + 4096, &tmXB, (s + 1) * 32, 1, sb + MB_XA);
                }
                bar_sync(BAR_O2, 256);
            }
            if (s == NSEG - 1) break;
            const uint32_t ln = laneid();
            auto softmax = [&](auto&& more) {
                const uint32_t pb = warp * 32 + (ln & 3) * 8, kt = min(ln >> 2, 4u);
                const uint32_t pw = keep(sb + OFF_PM + pb + selu(ln < 4, 0, pb + 256 + (~kt & 1) * 8 + ((kt + 1) & 4)));
                const uint32_t sr = keep(sb + OFF_SM + kt * 256 + (pb ^ (kt & 3) * 32));
                mbar_wait(sb + MB_S, s & 1);
                const float2 u = lds2f(sr), t = lds2f(sr + (OFF_SP - OFF_SM)), w = lds2f(sr + (OFF_SP + 1280 - OFF_SM));
                more();
                float x = u.x + t.x + w.x, y = u.y + t.y + w.y;
                const int m = __float_as_int(fmaxf(x, y)), hi = __reduce_max_sync(0xffffffffu, m), lw = __reduce_min_sync(0xffffffffu, m);
                const float mx = __int_as_float(hi >= 0 ? hi : lw) * -SCL_B;
                x = ex2(fmaf(x, SCL_B, mx)); y = ex2(fmaf(y, SCL_B, mx));
                sts1(pw, pack2(x, y));
                bar_sync(BAR_PM, 384);
            };
            if (act) {
                const uint32_t wo0 = keep(sb + OFF_WO + warp * 4096 + ((ln & 7) + ((ln >> 4) << 3)) * 64 + ((((ln >> 3) & 1) ^ ((ln >> 1) & 3)) << 4)), wo1 = keep(wo0 ^ 32);
                const uint32_t tag = (__shfl_sync(0xffffffffu, lds1(sb + OFF_EP), 0) ^ s) & 1;
                uint32_t f[24][4];
                auto ld = [&](int n) { ldsm4t((out_ord(n) & 1 ? wo1 : wo0) + (out_ord(n) >> 3) * 28672 + (out_ord(n) >> 1 & 3) * 1024, f[n][0], f[n][1], f[n][2], f[n][3]); };
#pragma unroll
                for (int n = 0; n < NPE; n++) ld(n);
                softmax([&]() {
#pragma unroll
                    for (int n = NPE; n < NPM; n++) ld(n);
                });
                if (s == 0) {
                    mbar_wait_long(sb + MB_WO, 0);
#pragma unroll
                    for (int n = 0; n < NPM; n++) ld(n);
                }
#pragma unroll
                for (int n = NPM; n < NPF; n++) ld(n);
                const uint32_t l8 = keep(sb + ln * 8);
                const char* dst = nullptr;
                blk(warp);
                bar_sync(BAR_O, 384);
                float2 bb[12];
                auto ldo = [&](int i) { bb[i] = lds2f(l8 + OFF_R1 + (i + 8) % 12 * 256); };
                float e[2][4] = {{0, 0, 0, 0}, {0, 0, 0, 0}};
                int nl = NPF, nb = 0;
#pragma unroll
                for (int n = 0; n < 24; n++) {
                    const int k = out_ord(n) >> 1, t = out_ord(n) & 1;
                    if (n == 8) { bar_sync(BAR_O2, 256); }
                    if (n == 0 || n == 8) { for (int i = 0; i < (n ? NO2 : NOB); i++) ldo(nb++); blk(warp); }
                    mma16(e[t], f[n][0], f[n][1], f[n][2], f[n][3], __float_as_uint(bb[k].x), __float_as_uint(bb[k].y));
                    if ((t || (OE && n >= 8)) && nb < (n < 8 ? 4 : 12)) ldo(nb++);
                    if (n > 1 && nl < 24 && !(n < 8 && n >= 8 - (NO2 - NOB + 1) / 2) && !(OE && n >= 8 && n < 8 + OE)) ld(nl++);
                    if (n == DN) { const uint32_t o = keep(l8); dst = keepp(win + (gp + ((o & 128) << 5) + (o & 127))); }
                    if (n == 23 || (LEAD && n == 24 - LEAD)) {
                        if (n < 23 || LEAD < 2) st_pkt8(dst, (pack2(e[0][0], e[0][1]) & ~1u) | tag, pack2(e[0][2], e[0][3]));
                        if (n == 23) st_pkt8(dst + 0x2000, (pack2(e[1][0], e[1][1]) & ~1u) | tag, pack2(e[1][2], e[1][3]));
                    }
                    if (t || out_ord(n + 1) % 2 == 0) blk(warp);
                }
            } else {
                softmax([]() { });
                if (warp != 7) { bar_arrive(BAR_O, 384); bar_arrive(BAR_O2, 256); }
                else {
                    const uint32_t now = (gtime() & ~31u) | ((s - lds1(sb + OFF_EP)) & 3);
                    const char* sp = win + (lds1(sb + OFF_SPO) + min(ln, 23u) * 16);
                    expect_e(sb + MB_XB, 4096);
                    bar_sync(BAR_O, 384);
                    asm volatile("fence.proxy.async.shared::cta;" ::: "memory");
                    uint4 sv = ld_pkt(sp);
                    tma3d_e(sb + OFF_MEMT + 8192, &tmXB, (s + 1) * 32, 2, sb + MB_XB);
                    mbar_wait(sb + MB_O, s & 1);
                    bar_arrive(BAR_O2, 256);
                    blk(s);
                    int d;
                    for (int c = 0; ; c++) {
                        const int d0 = sv.x - now, d1 = sv.y - now, d2 = sv.z - now, d3 = sv.w - now;
                        d = max(max(d0, d1), max(d2, d3));
                        if (!__any_sync(0xffffffffu, (d0 | d1 | d2 | d3) & 2) || c == 512) break;
                        sv = ld_pkt(sp);
                    }
                    sts1(sb + OFF_T, (now + min(__reduce_max_sync(0xffffffffu, d), 8192)) & ~31u);
                    bar_arrive(BAR_G, 64);
                    mbar_wait(sb + MB_XA, (s + 1) & 1);
                }
            }
        }
        asm volatile("setmaxnreg.dec.sync.aligned.u32 168;");
        uint32_t f[24][4];
        const uint32_t lnt = laneid(), ep = lds1(sb + OFF_EP);
        {
            const uint32_t wo0 = sb + OFF_WO + warp * 4096 + ((lnt & 7) + ((lnt >> 4) << 3)) * 64 + ((((lnt >> 3) & 1) ^ ((lnt >> 1) & 3)) << 4);
#pragma unroll
            for (int n = 0; n < 24; n++) ldsm4t((wo0 ^ (n / 12) * 32) + (n % 12 >> 2) * 28672 + (n & 3) * 1024, f[n][0], f[n][1], f[n][2], f[n][3]);
        }
        char* tp = reinterpret_cast<char*>(g_tail) + head * 40960 + box * 2048 + lnt * 16;
#pragma unroll 1
        for (int t = 0; t < 2; t++) {
            const uint32_t b0 = (((sb + (t ? OFF_OXL : OFF_OX)) & 0x3FFFF) >> 4) | (1u << 16), b1 = (((sb + OFF_OXG + t * 8192) & 0x3FFFF) >> 4) | (1u << 16);
            float acc[2][16];
#pragma unroll
            for (int i = 0; i < 16; i++) acc[0][i] = acc[1][i] = 0.f;
            auto st = [&](int i) {
                const float* a = acc[i];
                st_pkt(tp + i * 1024, make_uint4((pack2(a[0], a[1]) & ~1u) | (ep & 1), pack2(a[2], a[3]), pack2(a[4], a[5]), pack2(a[6], a[7])));
                st_pkt(tp + i * 1024 + 512, make_uint4((pack2(a[8], a[9]) & ~1u) | (ep & 1), pack2(a[10], a[11]), pack2(a[12], a[13]), pack2(a[14], a[15])));
            };
            if (t) bar_sync(BAR_WO, 384);
            wg_fence();
            static_for<0, 8>([&](auto N) {
                constexpr int i = N.value >> 2, k = N.value & 3;
                wgmma_rs32<k * 2, k != 0>(acc[i], f[12 * i + k][0], f[12 * i + k][1], f[12 * i + k][2], f[12 * i + k][3], b0);
            });
            wg_commit();
            mbar_wait(sb + MB_F + 8 * t, 0);
            if (t) asm volatile("barrier.cluster.arrive.relaxed.aligned;" ::: "memory");
            static_for<0, 2>([&](auto I) {
                constexpr int i = I.value;
                wg_fence();
                static_for<4, 12>([&](auto K) {
                    constexpr int k = K.value;
                    wgmma_rs32<(k / 4 - 1) * 256 + (k & 3) * 2, 1>(acc[i], f[12 * i + k][0], f[12 * i + k][1], f[12 * i + k][2], f[12 * i + k][3], b1);
                });
                wg_commit();
            });
            wg_wait<1>();
            if (act) st(0);
            wg_wait<0>();
            if (act) st(1);
            if (t) bar_arrive(BAR_X, 384);
            tp += 32 * 40960;
        }
    } else {
        asm volatile("setmaxnreg.dec.sync.aligned.u32 56;");
        const int g = __reduce_max_sync(0xffffffffu, (unsigned)tid >> 5 & 3);
        if (g >= 2) pick_role(sb, false, g & 1, pp, ep0 + 1);
        const uint32_t ep = __reduce_max_sync(0xffffffffu, ep0) + 1;
        sts1(sb + OFF_EP, ep);
#pragma unroll
        for (int i = 0; i < 5; i++) {
            const unsigned short* m = reinterpret_cast<const unsigned short*>(mem0) + g * 160 + (tid & 31) + 32 * i;
            sts4(sb + (tid & 127) * 16 + (i < 4 ? OFF_SX + i * 2048 : OFF_WO + 81920),
                 make_uint4(m[0] | ((uint32_t)m[DM] << 16), m[2 * DM] | ((uint32_t)m[3 * DM] << 16),
                            m[4 * DM] | ((uint32_t)m[5 * DM] << 16), m[6 * DM] | ((uint32_t)m[7 * DM] << 16)));
        }
        asm volatile("barrier.cluster.wait.acquire.aligned;" ::: "memory");
        if (g == 0) {
            const int e0 = head * DH + rank * 64;
            for (int i = PWIN; i < 5; i++) {
                mbar_wait(sb + MB_F + 8 * (i - PWIN), 0);
                expect_e(sb + MB_F + 8 * i, 32768);
                tma2d_e(sb + OFF_WV + i * 16384, &tmWq, e0, i * 128, sb + MB_F + 8 * i);
                tma2d_e(sb + OFF_WO + i * 16384, &tmWk, e0, i * 128, sb + MB_F + 8 * i);
            }
            for (int i = 0; i < 5; i++) {
                mbar_wait(sb + MB_E + 8 * i, 0);
                if (i + 5 - PWIN < 5) mbar_wait(sb + MB_F + 8 * (i + 5 - PWIN), 0);
                expect_e(sb + MB_F + 8 * i, 16384);
                tma2d_e(sb + OFF_WV + i * 16384, &tmWv, e0, i * 128, sb + MB_F + 8 * i);
            }
        }
        uint32_t role = 0, ph = 0, tg = 0;
        uint32_t o16 = __shfl_sync(0xffffffffu, (tid & 31) * 16, tid & 31);
        auto gather = [&](int s) {
            const char* mb = win + (role >> 8 & 1) * 4096 + xch_copy((role >> 1) % NCP);
            mbar_wait(sb + MB_EM, s & 1);
            ggate(tg + G2);
            pause<F2>();
#pragma unroll
            for (int i = 0; i < 4; i++) { const int c = (i & 1) * 2 + (i >> 1); bulk_ld_e(sb + OFF_MEMT + c * 2560, mb + xch_mem(c), 2560, sb + MB_M + 8 * c); }
            bar_arrive(BAR_G, 64);
        };

        for (int s = 0; ; s++) {
            uint32_t vx[8];
            o16 += opq0<8>(s);
            const uint32_t lz = sb + o16;
            const uint4* vp = keepp(g_vx + (blockIdx.x * 64 + s) * 256 + g * 32 + (o16 >> 4));
            auto load_v = [&]() {
                const uint4 u = ld_pkt(vp), v = ld_pkt(vp + 128);
                vx[0] = u.x; vx[2] = u.y; vx[1] = u.z; vx[3] = u.w; vx[4] = v.x; vx[6] = v.y; vx[5] = v.z; vx[7] = v.w;
            };
            const char* mb = win + (role >> 8 & 1) * 4096 + xch_copy((role >> 1) % NCP);
            auto store_x = [&]() {
                if (g == 3) {
                    bar_sync(BAR_G, 64);
                    if (o16 == 0 && s < NSEG - 1) { tma_st(&tmOx, sb + OFF_OX, blockIdx.x * 64, (s - 1) * 32); asm volatile("cp.async.bulk.commit_group;" ::: "memory"); }
                    __syncwarp();
                }
            };
#pragma unroll
            for (int j = 0; j < 8; j++) vx[j] = 0;
            if (s > NVC) load_v();
            if (s >= NVC) store_x();
            if (s < NVC) {
                const uint32_t wv_lo = (((sb + OFF_WV) & 0x3FFFF) >> 4) | (64u << 16), xr_lo = (((sb + OFF_XR) & 0x3FFFF) >> 4) | (1u << 16);
                float acc[16];
#pragma unroll
                for (int i = 0; i < 16; i++) acc[i] = 0.f;
                mbar_wait(sb + MB_XA, s & 1);
                mbar_wait(sb + MB_XB, s & 1);
                static_for<0, 10>([&](auto KB) {
                    constexpr uint32_t kb = KB.value;
                    if (kb == 4) {
                        wg_wait<1>();
                        bar_sync(BAR_P, 128);
                        if (s > 0) { if (g == 1) gather(s); store_x(); }
                        else {
                            const uint32_t ln = laneid();
                            mbar_wait_long(sb + MB_EM, 0);
#pragma unroll
                            for (int i = 0; i < 5; i++)
                                sts4(sb + mem_row(ln) + OFF_MEMT + g * 2560 + 512 * i, lds4(sb + g * 512 + ln * 16 + (i < 4 ? OFF_SX + i * 2048 : OFF_WO + 81920)));
                            asm volatile("fence.proxy.async.shared::cta;" ::: "memory");
                            bar_sync(BAR_P, 128);
                            arrive_e(sb + MB_M + 8 * g);
                        }
                    }
                    if (!(kb & 1) && s == 0) {
                        mbar_wait_long(sb + MB_E + 4 * kb, 0);
                        mbar_wait_long(sb + MB_F + 4 * kb, 1);
#pragma unroll
                        for (int p = 0; p < 3; p++)
                            if (kb == (WOK >> 4 * p & 15) && g == 0) tma3d_e(sb + OFF_WO + p * 28672, &tmWo, head * DH + (rank + p) % 3 * 64, rank * 7, sb + MB_WO);
                    }
                    wg_fence();
                    static_for<0, 4>([&](auto K4) { wgmma_ss32<(kb * 4 + K4.value) * 128, xblk(kb) / 16 + K4.value * 2, (kb | K4.value) != 0>(acc, wv_lo, xr_lo); });
                    wg_commit();
                });
                wg_wait<0>();
#pragma unroll
                for (int j = 0; j < 8; j++) vx[j] = pack2(acc[2 * j], acc[2 * j + 1]);
                bar_sync(BAR_P, 128);
            }
            const uint32_t* fv = g_flagv + blockIdx.x * 64 + (s == NVC ? s : s + 1);
            uint32_t fl = ep;
            if (s == NVC || (g == 0 && s > NVC && (VFLAGS >> 1 >> s & 1))) fl = ld_relaxed(fv);
            {
                const uint32_t mt = keep(sb + OFF_MEMT + g * 2560 + o16 * 2 + (o16 >> 4 & 28)), tag = (s ^ ep ^ 1) & 1, msk = keep(s > 0);
                const int bar = keep(BAR_MEM + g);
                auto stale = [&](uint32_t m) {
                    const uint32_t w0 = lds1(mt), w1 = lds1(mt + 1024), w2 = lds1(mt + 1536);
                    return arrive_unless(tagx(w0, w1, tag) | (w2 ^ tag), m, bar, 160);
                };
                mbar_wait_long(sb + MB_M + 8 * g, s & 1);
                if (stale(msk)) {
                    for (int cnt = 0; ; cnt++) {
                        bulk_ld_e(sb + OFF_MEMT + g * 2560, mb + xch_mem(g), 2560, sb + MB_M2 + 8 * g);
                        expect_e(sb + MB_M2 + 8 * g, 2560);
                        mbar_wait_long(sb + MB_M2 + 8 * g, ph);
                        ph ^= 1;
                        if (!stale(cnt < WAIT_LIM)) break;
                    }
                }
            }
            if (g == 3) { asm volatile("cp.async.bulk.wait_group.read 0;" ::: "memory"); __syncwarp(); bar_arrive(BAR_R1, 288); if (RB) bar_arrive(BAR_PM, 160); }
            if (g == XG && s < NSEG - 1) {
                mbar_wait(sb + MB_EA, s & 1);
                expect_e(sb + MB_XA, NX * 4096);
                tma3d_e(sb + OFF_XR, &tmXA, (s + 1) * 32, 3, sb + MB_XA);
            }
            if (fl != ep) for (int c = 0; c < SPIN_LIM && ld_acquire(fv) != ep; c++) { }
            if (s == NVC) load_v();
            if (PFV && g == 0 && s >= NVC && s < NSEG - 1) asm volatile("prefetch.global.L2 [%0];" :: "l"(g_vx + (blockIdx.x * 64 + s + 1) * 256 + (o16 >> 1)));
            if (s < NSEG - 1) {
                if (g == 0) expect_e(sb + MB_O, 2048);
            } else if (g == 0) {
                expect_e(sb + MB_F, 8192); expect_e(sb + MB_F + 8, 8192);
            }
            if (g == 1) expect_e(sb + MB_SX, 5120);
            auto progress = [&]() {
                if (g == 3 && (PROG >> s & 1)) {
                    if (o16 == 0) {
                        asm volatile("cp.async.bulk.wait_group 0;" ::: "memory");
                        st_pkt4(g_prog + blockIdx.x + (keep(s) >> 8), ep * 128 + s);
                    }
                    __syncwarp();
                }
            };
            progress();
            const uint32_t q1 = keep(mapa(sb, (rank + 1) % 3) - sb), q2 = keep(mapa(sb, (rank + 2) % 3) - sb);
            uint32_t own[5], vm0, vm1;
            {
                const uint32_t qa_lo = (((sb + OFF_QA + 1024) & 0x3FFFF) >> 4) | (1u << 16), ka_lo = (((sb + OFF_KA) & 0x3FFFF) >> 4) | (1u << 16);
                const uint32_t va = keep(sb + ((o16 >> 1) ^ g * 32) + g * 256 + (s == NSEG - 1 ? OFF_R1L : OFF_R1) + 2048);
                float d[20];
#pragma unroll
                for (int j = 0; j < 20; j++) d[j] = 0.f;
                bar_sync(BAR_S, 288);
                const float2 u = lds2f(va), v = lds2f(va + 1024);
                role = __shfl_sync(0xffffffffu, lds1(sb + OFF_ROLE), 0);
                asm volatile("fence.proxy.async.shared::cta;" ::: "memory");
                wg_fence();
                static_for<0, 4>([&](auto K4) { wgmma_ss40<K4.value * 2, K4.value != 0>(d, qa_lo, ka_lo); });
                wg_commit();
                if (s < NSEG - 1) expect_e(sb + MB_M + 8 * g, 2560);
                vm0 = badd2(__float_as_uint(u.x), __float_as_uint(v.x)); vm1 = badd2(__float_as_uint(u.y), __float_as_uint(v.y));
                const uint32_t xo = lz + OFF_SX + g * 640, mo = sb + OFF_SX + g * 640 + 512 + (o16 >> 2);
                const int lim = 8 + 8 * g + (o16 >> 6) - ((o16 >> 3) & 6);
                wg_wait<0>();
#pragma unroll
                for (int j = 0; j < 5; j++) own[j] = pack2(8 * j > lim ? -INFINITY : d[4 * j], 8 * j + 1 > lim ? -INFINITY : d[4 * j + 1]);
                mbar_wait(sb + MB_S, s & 1);
                st_async4(q1 + xo + 2560, own[0], own[1], own[2], own[3], q1 + sb + MB_SX); st_async4(q2 + xo, own[0], own[1], own[2], own[3], q2 + sb + MB_SX);
                st_async1(q1 + mo + 2560, own[4], q1 + sb + MB_SX);                         st_async1(q2 + mo, own[4], q2 + sb + MB_SX);
            }
            if (s < NSEG - 1) {
                const uint32_t pm = keep(sb + OFF_PM + (o16 >> 1)), oo = keep(pm + (OFF_R1 - OFF_PM) + g * 256);
                blk(s);
                bar_sync(BAR_PM, 384);
                const uint4 qq = lds4(lz + OFF_PM + 256);
                const uint32_t p0 = lds1(pm);
                float oa[2][4] = {{0, 0, 0, 0}, {0, 0, 0, 0}}, ob[2][4] = {{0, 0, 0, 0}, {0, 0, 0, 0}}, os[4] = {0, 0, 0, 0};
                mma16(os, qq.x, qq.y, qq.z, qq.w, 0x3f803f80, 0x3f803f80);
                mma16(oa[0], qq.x, qq.y, qq.z, qq.w, vx[0], vx[2]);
                mma16(oa[1], qq.x, qq.y, qq.z, qq.w, vx[1], vx[3]);
                mma16(ob[0], qq.x, qq.y, qq.z, qq.w, vx[4], vx[6]);
                mma8(os, p0, 0, 0x3f803f80);
                mma16(ob[1], qq.x, qq.y, qq.z, qq.w, vx[5], vx[7]);
                mma8(oa[0], p0, 0, vm0);
                mma8(oa[1], p0, 0, vm1);
                const float inv = rcpf(os[0] + os[2]);
                const uint32_t o0 = pack2((oa[0][0] + ob[0][2]) * inv, (oa[0][1] + ob[0][3]) * inv), o1 = pack2((oa[1][0] + ob[1][2]) * inv, (oa[1][1] + ob[1][3]) * inv);
                st_async2(q1 + oo + 1024, o0, o1, q1 + sb + MB_O);
                st_async2(q2 + oo, o0, o1, q2 + sb + MB_O);
                sts2(oo + 2048, o0, o1);
                bar_arrive(BAR_O, 384);
            } else if (g == 1) {
                share_o(sb, rank, OFF_OX, 0);
            }
            {
                float sc[10], mx;
                const uint32_t xo = lz + OFF_SX + g * 640, pa = sb + OFF_SX + g * 640 + (o16 >> 2);
                mbar_wait(sb + MB_SX, s & 1);
                const uint4 u = lds4(xo), v = lds4(xo + 2560);
                const uint32_t um = lds1(pa + 512), vm = lds1(pa + 512 + 2560);
#define SSUM(k, a, b, c) sc[k] = (bf_lo(a) + bf_lo(b)) + bf_lo(c); sc[k + 1] = (bf_hi(a) + bf_hi(b)) + bf_hi(c);
                SSUM(0, own[0], u.x, v.x) SSUM(2, own[1], u.y, v.y) SSUM(4, own[2], u.z, v.z) SSUM(6, own[3], u.w, v.w) SSUM(8, own[4], um, vm)
#undef SSUM
                mx = fmaxf(fmaxf(fmaxf(sc[2], sc[3]), fmaxf(sc[4], sc[5])), fmaxf(fmaxf(fmaxf(sc[6], sc[7]), fmaxf(sc[8], sc[9])), fmaxf(sc[0], sc[1])));
                mx = fmaxf(fmaxf(mx, __shfl_xor_sync(0xffffffffu, mx, 1)), fmaxf(__shfl_xor_sync(0xffffffffu, mx, 2), __shfl_xor_sync(0xffffffffu, mx, 3)));
                mx *= -SCL_B;
                float sum = 0.f;
#pragma unroll
                for (int j = 0; j < 10; j++) { sc[j] = ex2(fmaf(sc[j], SCL_B, mx)); sum += sc[j]; }
                sum = (sum + __shfl_xor_sync(0xffffffffu, sum, 1)) + (__shfl_xor_sync(0xffffffffu, sum, 2) + __shfl_xor_sync(0xffffffffu, sum, 3));
                const float inv = rcpf(sum);
#pragma unroll
                for (int j = 0; j < 5; j++) sts1(pa + j * 128, pack2(sc[2 * j] * inv, sc[2 * j + 1] * inv));
                asm volatile("fence.proxy.async.shared::cta;" ::: "memory");
            }
            float acc[16];
            {
                const uint32_t px_lo = (((sb + OFF_SX) & 0x3FFFF) >> 4) | (8u << 16);
                uint32_t a[12];
                const uint32_t z = opq0<8>(s);
#pragma unroll
                for (int i = 0; i < 12; i++) asm volatile("xor.b32 %0, %1, %2;" : "=r"(a[i]) : "r"(i < 8 ? vx[i & 7] : i == 8 ? vm0 : i == 9 ? vm1 : 0u), "r"(z));
#pragma unroll
                for (int i = 0; i < 16; i++) acc[i] = 0.f;
                if (g == 1 && s < NSEG - 1) { bar_sync(BAR_G, 64); tg = lds1(sb + OFF_T); }
                if (s < NSEG - 1) bar_sync(BAR_WO, 384); else bar_sync(BAR_P, 128);
                wg_fence();
                wgmma_rs32n<0, 0>(acc, a[8], a[9], a[10], a[11], px_lo);
                wgmma_rs32n<8, 1>(acc, a[0], a[1], a[2], a[3], px_lo);
                wgmma_rs32n<24, 1>(acc, a[4], a[5], a[6], a[7], px_lo);
                wg_commit();
            }
            o16 += opq0<9>(s);
            const uint32_t ln = o16 >> 4;
            const uint32_t sa = keep(sb + (s == NSEG - 1 ? OFF_OXL : OFF_OX) + ((ln & 7) + ((ln >> 4) << 3)) * 128 + (((2 * g + ((ln >> 3) & 1)) ^ (ln & 7)) << 4));
            auto store_o = [&]() {
                wg_wait<0>();
                stsm4t(sa, pack2v(acc[0], acc[1]), pack2v(acc[2], acc[3]), pack2v(acc[4], acc[5]), pack2v(acc[6], acc[7]));
                stsm4t(sa + 2048, pack2v(acc[8], acc[9]), pack2v(acc[10], acc[11]), pack2v(acc[12], acc[13]), pack2v(acc[14], acc[15]));
            };
            if ((role & 255) < 80 && s < NSEG - 1) {
                const char* rp = keepp(win + (XCH_PART + (role & 255) * 4096 + g * 1024 + (o16 >> 1)));
                const char* wp = keepp(win + ((role >> 9 << 7) + (((o16 >> 4 ^ role) & 1) * 4 + (o16 >> 7)) * 16 + (o16 >> 3 & 12)));
                const uint32_t tag = (s ^ ep) & 1, rb = keep(sb + (o16 >> 1));
                uint32_t x[4], y[4];
                auto load = [&]() { static_for<0, 4>([&](auto I) { ld_pkt8<I.value * 256>(x[I.value], y[I.value], rp); }); };
                auto sum8 = [&](uint32_t m) {
                    sts4(sb + o16 + OFF_RED + g * 512,
                         make_uint4(__float_as_uint(((bf_lo(x[0]) + bf_lo(x[1])) + bf_lo(x[2])) + bf_lo(x[3])), __float_as_uint(((bf_hi(x[0]) + bf_hi(x[1])) + bf_hi(x[2])) + bf_hi(x[3])),
                                    __float_as_uint(((bf_lo(y[0]) + bf_lo(y[1])) + bf_lo(y[2])) + bf_lo(y[3])), __float_as_uint(((bf_hi(y[0]) + bf_hi(y[1])) + bf_hi(y[2])) + bf_hi(y[3]))));
                    return sync_unless(tagx(x[0], x[1], tag), tagx(x[2], x[3], tag), m, BAR_R, 128);
                };
                auto again = [&]() { for (int cnt = 0; ; cnt++) { load(); if (!sum8(cnt < WAIT_LIM)) break; } };
                if (g == 0) {
                    bar_sync(BAR_R, 128);
                    load();
                    store_o();
                    const bool st = sum8(1);
                    float2 r[8];
#pragma unroll
                    for (int i = 0; i < 8; i++) r[i] = lds2f(rb + OFF_RED + i * 256);
                    if (REL == 1 && s >= NVC - 1) bar_arrive(BAR_PUB, 288);
                    if (st) {
                        again();
#pragma unroll
                        for (int i = 0; i < 8; i++) r[i] = lds2f(rb + OFF_RED + i * 256);
                    }
                    const float k0 = ((r[0].x + r[1].x) + (r[2].x + r[3].x)) + ((r[4].x + r[5].x) + (r[6].x + r[7].x));
                    const float k1 = ((r[0].y + r[1].y) + (r[2].y + r[3].y)) + ((r[4].y + r[5].y) + (r[6].y + r[7].y));
                    const uint32_t kb = __float_as_uint(k0);
                    const uint32_t pk = __byte_perm(kb + ((kb ^ tag << 16) & 0x10000), pack2(0.f, k1), 0x7632);
#pragma unroll
                    for (int i = 0; i < 2 * NCP; i++) st_pkt4(wp + xch_copy(i >> 1) + (i & 1) * 4096, pk);
                    if (REL == 2 && s >= NVC - 1) bar_arrive(BAR_PUB, 288);
                } else {
                    if (g == 1) { ggate(tg + G1); pause<F1>(); }
                    bar_sync(BAR_R, 128);
                    load();
                    store_o();
                    if (sum8(1)) again();
                }
            } else {
                store_o();
                if (s == NSEG - 1) {
                    asm volatile("fence.proxy.async.shared::cta;" ::: "memory");
                    bar_arrive(BAR_WO, 384);
                    bar_sync(BAR_P, 128);
                    if (g == 1) share_o(sb, rank, OFF_OXL, 1);
                    break;
                }
                bar_sync(BAR_R, 128);
                if (g == 0 && s >= NVC - 1) bar_arrive(BAR_PUB, 288);
            }
            if (g == 1 && s >= NVC - 1) gather(s + 1);
            if (g == 3) asm volatile("fence.proxy.async.shared::cta;" ::: "memory");
        }
        uint32_t u, c, sb2;
        asm volatile("mov.u32 %0, %%tid.x; mov.u32 %1, %%ctaid.x; mov.u32 %2, %%dynamic_smem_size;" : "=r"(u), "=r"(c), "=r"(sb2));
        sb2 += sb - CHAIN_SMEM;
        const uint32_t g2 = __shfl_sync(0xffffffffu, (u >> 5) & 3, 0), ln = u & 31;
        asm volatile("barrier.cluster.arrive.relaxed.aligned;" ::: "memory");
        asm volatile("setmaxnreg.inc.sync.aligned.u32 96;");
        const uint32_t et = lds1(sb2 + OFF_EP);
        const uint4* rp = g_tail + g2 * 8 * 2560 + c * 32 + ln;
        bf16* op = out + (size_t)((NSEG - 2) * 32 + (c & 1) * 16 + (g2 >> 1) * 8 + (ln >> 2)) * OUTW + DM + (c >> 1) * 16 + (g2 & 1) * 8 + (ln & 3) * 2;
#pragma unroll 1
        for (int t = 0; t < 2; t++) {
            if (t) bar_sync(BAR_X, 384);
            if (c >= 80) continue;
            spin(t ? TXE : TXD);
            uint4 q[8];
#pragma unroll
            for (int i = 0; i < 8; i++) q[i] = ld_pkt(rp + 2560 * i);
            for (int cnt = 4 * WAIT_LIM; cnt; cnt--) {
                uint32_t bad = 0;
#pragma unroll
                for (int i = 0; i < 8; i++) bad |= q[i].x ^ et;
                if (!any_bit0(bad, bad)) break;
                static_for<0, 8>([&](auto I) { ld_pkt_stale<I.value * 40960>(q[I.value], rp, et); });
            }
            float r[8] = {0, 0, 0, 0, 0, 0, 0, 0};
#pragma unroll
            for (int i = 0; i < 8; i++) {
                r[0] += bf_lo(q[i].x); r[1] += bf_hi(q[i].x); r[2] += bf_lo(q[i].y); r[3] += bf_hi(q[i].y);
                r[4] += bf_lo(q[i].z); r[5] += bf_hi(q[i].z); r[6] += bf_lo(q[i].w); r[7] += bf_hi(q[i].w);
            }
            const uint32_t ra = sb2 + OFF_TRED + t * 4096 + ln * 8, rb2 = ra + g2 * 1024;
#pragma unroll
            for (int j = 0; j < 4; j++) sts2(ra + j * 1024 + g2 * 256, __float_as_uint(r[2 * j]), __float_as_uint(r[2 * j + 1]));
            bar_sync(BAR_R, 128);
            const float2 x0 = lds2f(rb2), x1 = lds2f(rb2 + 256), x2 = lds2f(rb2 + 512), x3 = lds2f(rb2 + 768);
            stg1(op, movm(pack2((x0.x + x1.x) + (x2.x + x3.x), (x0.y + x1.y) + (x2.y + x3.y))));
            rp += 32 * 2560;
            op += 32 * OUTW;
        }
    }
    asm volatile("barrier.cluster.wait.aligned;" ::: "memory");
}

constexpr int NSIDE = 36, SST = 3, MAXJ = 44, NKS = 7;
constexpr uint32_t S_STAGE = 49152, S_STG = SST * S_STAGE, S_RST = S_STG + 65536, S_BAR = S_RST + 12288, SIDE_SMEM = S_BAR + 256;
constexpr uint32_t SB_FULL = S_BAR, SB_EMPTY = S_BAR + 64, SB_STAGED = S_BAR + 32, SB_FREE = S_BAR + 48;
constexpr uint32_t SB_FINE = 128;
enum { JV = 0, JQ = 1, JP = 2, JO = 3, JR = 4, JEND = 5 };
struct SideParams {
    bf16* out;
    CUtensorMap a[4], b[4], c[4], st[2], sto;
};
struct Job { uint32_t x, y; };
struct JobTable { Job j[NSIDE][MAXJ]; };
static_assert(OFF_OX % 1024 == 0 && OFF_QA % 1024 == 0 && OFF_MEMT % 1024 == 0, "swizzled tiles");
__constant__ const JobTable c_jobs = {{
    {{0x4020,0xa0000},{0x5220,0xa0000},{0xcc20,0xa0000},{0x641,0xa0000},{0x10341,0xa0000},{0x20640,0xa0000},{0x43,0x600000},{0x51540,0xa0000},{0x602c0,0xa0000},{0x60d40,0xa0000},{0x617c0,0xa0000},{0x40043,0x10e0400},{0x70340,0xa0000},{0x71040,0xa0000},{0x50043,0x10e0500},{0x60023,0x10e0600},{0x2360223,0x10d0605},{0x70023,0x10e0800},{0x78013,0x10e0900},{0x70024,0x1000800},{0x70224,0x1000802},{0x5,0x0},{0x40044,0x1000400},{0x50044,0x1000500},{0x60024,0x1000600},{0x68024,0x1000700}},
    {{0x40a0,0xa0000},{0x52a0,0xa0000},{0xcca0,0xa0000},{0x6c1,0xa0000},{0x103c1,0xa0000},{0x206c0,0xa0000},{0xc3,0x600000},{0x515c0,0xa0000},{0x60340,0xa0000},{0x60dc0,0xa0000},{0x50042,0xa0000},{0x400c3,0x10e0400},{0x703c0,0xa0000},{0x710c0,0xa0000},{0x500c3,0x10e0500},{0x600a3,0x10e0600},{0x680a3,0x10e0700},{0x700a3,0x10e0800},{0x78093,0x10e0900},{0x700a4,0x1000800},{0x78094,0x1000900},{0x5,0x0},{0x400c4,0x1000400},{0x500c4,0x1000500},{0x600a4,0x1000600},{0x680a4,0x1000700}},
    {{0x4120,0xa0000},{0x5320,0xa0000},{0xcd20,0xa0000},{0x741,0xa0000},{0x10441,0xa0000},{0x20740,0xa0000},{0x143,0x600000},{0x51640,0xa0000},{0x603c0,0xa0000},{0x60e40,0xa0000},{0x500c2,0xa0000},{0x40143,0x10e0400},{0x70440,0xa0000},{0x71140,0xa0000},{0x50143,0x10e0500},{0x60123,0x10e0600},{0x68123,0x10e0700},{0x70123,0x10e0800},{0x78113,0x10e0900},{0x70124,0x1000800},{0x78114,0x1000900},{0x5,0x0},{0x40144,0x1000400},{0x50144,0x1000500},{0x60124,0x1000600},{0x68124,0x1000700}},
    {{0x41a0,0xa0000},{0x53a0,0xa0000},{0xcda0,0xa0000},{0x14030,0xa0000},{0x150b0,0xa0000},{0x20341,0xa0000},{0x20dc0,0xa0000},{0x30541,0xa0000},{0x505c1,0xa0000},{0x30dc0,0xa0000},{0x602c1,0xa0000},{0x705c1,0xa0000},{0x408c0,0xa0000},{0x415c0,0xa0000},{0x505c0,0xa0000},{0x51040,0xa0000},{0x40042,0xa0000},{0x60840,0xa0000},{0x612c0,0xa0000},{0x401c3,0x10e0400},{0x600c2,0xa0000},{0x70b40,0xa0000},{0x501c3,0x10e0500},{0x700c2,0xa0000},{0x681a3,0x10e0700},{0x701a3,0x10e0800},{0x78193,0x10e0900},{0x701a4,0x1000800},{0x78194,0x1000900},{0x5,0x0},{0x401c4,0x1000400},{0x501c4,0x1000500},{0x601a4,0x1000600},{0x681a4,0x1000700}},
    {{0x4220,0xa0000},{0x5420,0xa0000},{0xce20,0xa0000},{0x140b0,0xa0000},{0x15130,0xa0000},{0x203c1,0xa0000},{0x20e40,0xa0000},{0x305c1,0xa0000},{0x50641,0xa0000},{0x30e40,0xa0000},{0x60341,0xa0000},{0x70641,0xa0000},{0x40940,0xa0000},{0x41640,0xa0000},{0x50640,0xa0000},{0x510c0,0xa0000},{0x400c2,0xa0000},{0x608c0,0xa0000},{0x61340,0xa0000},{0x40243,0x10e0400},{0x60142,0xa0000},{0x70bc0,0xa0000},{0x50243,0x10e0500},{0x70142,0xa0000},{0x68223,0x10e0700},{0x70223,0x10e0800},{0x78213,0x10e0900},{0x70224,0x1000800},{0x78214,0x1000900},{0x5,0x0},{0x40244,0x1000400},{0x50244,0x1000500},{0x60224,0x1000600},{0x68224,0x1000700}},
    {{0x42a0,0xa0000},{0x54a0,0xa0000},{0xcea0,0xa0000},{0x14130,0xa0000},{0x151b0,0xa0000},{0x20441,0xa0000},{0x20ec0,0xa0000},{0x30641,0xa0000},{0x506c1,0xa0000},{0x30ec0,0xa0000},{0x603c1,0xa0000},{0x706c1,0xa0000},{0x409c0,0xa0000},{0x416c0,0xa0000},{0x506c0,0xa0000},{0x51140,0xa0000},{0x40142,0xa0000},{0x60940,0xa0000},{0x613c0,0xa0000},{0x740043,0x10e0401},{0x601c2,0xa0000},{0x70c40,0xa0000},{0x750043,0x10e0501},{0x701c2,0xa0000},{0x768023,0x10e0701},{0x770023,0x10e0801},{0x778013,0x10e0901},{0x70024,0x1000801},{0x78014,0x1000901},{0x5,0x0},{0x40044,0x1000401},{0x50044,0x1000501},{0x60024,0x1000601},{0x68024,0x1000701}},
    {{0x4320,0xa0000},{0x5520,0xa0000},{0xcf20,0xa0000},{0x141b0,0xa0000},{0x15230,0xa0000},{0x204c1,0xa0000},{0x20f40,0xa0000},{0x306c1,0xa0000},{0x50741,0xa0000},{0x30f40,0xa0000},{0x60441,0xa0000},{0x70741,0xa0000},{0x40a40,0xa0000},{0x41740,0xa0000},{0x50740,0xa0000},{0x511c0,0xa0000},{0x401c2,0xa0000},{0x609c0,0xa0000},{0x61440,0xa0000},{0x7400c3,0x10e0401},{0x60242,0xa0000},{0x70cc0,0xa0000},{0x7500c3,0x10e0501},{0x70242,0xa0000},{0x7680a3,0x10e0701},{0x7700a3,0x10e0801},{0x778093,0x10e0901},{0x700a4,0x1000801},{0x78094,0x1000901},{0x5,0x0},{0x400c4,0x1000401},{0x500c4,0x1000501},{0x600a4,0x1000601},{0x680a4,0x1000701}},
    {{0x43a0,0xa0000},{0x55a0,0xa0000},{0xcfa0,0xa0000},{0x14230,0xa0000},{0x152b0,0xa0000},{0x20541,0xa0000},{0x20fc0,0xa0000},{0x30741,0xa0000},{0x30040,0xa0000},{0x30fc0,0xa0000},{0x604c1,0xa0000},{0x10042,0xa0000},{0x40ac0,0xa0000},{0x417c0,0xa0000},{0x507c0,0xa0000},{0x51240,0xa0000},{0x40242,0xa0000},{0x60a40,0xa0000},{0x614c0,0xa0000},{0x740143,0x10e0401},{0x70040,0xa0000},{0x70d40,0xa0000},{0x750143,0x10e0501},{0x760123,0x10e0601},{0x7600a3,0x10e0601},{0x768123,0x10e0701},{0x770123,0x10e0801},{0x778113,0x10e0901},{0x78114,0x1000901},{0x5,0x0},{0x40144,0x1000401},{0x50144,0x1000501},{0x60124,0x1000601},{0x68124,0x1000701}},
    {{0x4420,0xa0000},{0x5620,0xa0000},{0xd020,0xa0000},{0x142b0,0xa0000},{0x15330,0xa0000},{0x205c1,0xa0000},{0x21040,0xa0000},{0x40041,0xa0000},{0x300c0,0xa0000},{0x31040,0xa0000},{0x60541,0xa0000},{0x100c2,0xa0000},{0x40b40,0xa0000},{0x20043,0x600200},{0x71340,0xa0000},{0x7501c3,0x10e0501},{0x7601a3,0x10e0601},{0x7681a3,0x10e0701},{0x7701a3,0x10e0801},{0x778193,0x10e0901},{0x701a4,0x1000801},{0x78194,0x1000901},{0x5,0x0},{0x401c4,0x1000401},{0x501c4,0x1000501},{0x601a4,0x1000601},{0x681a4,0x1000701}},
    {{0x44a0,0xa0000},{0x56a0,0xa0000},{0xd0a0,0xa0000},{0x14330,0xa0000},{0x153b0,0xa0000},{0x20641,0xa0000},{0x210c0,0xa0000},{0x400c1,0xa0000},{0x30140,0xa0000},{0x310c0,0xa0000},{0x605c1,0xa0000},{0x10142,0xa0000},{0x40bc0,0xa0000},{0x200c3,0x600200},{0x713c0,0xa0000},{0x750243,0x10e0501},{0x760223,0x10e0601},{0x768223,0x10e0701},{0x770223,0x10e0801},{0x778213,0x10e0901},{0x70224,0x1000801},{0x78214,0x1000901},{0x5,0x0},{0x40244,0x1000401},{0x50244,0x1000501},{0x60224,0x1000601},{0x68224,0x1000701}},
    {{0x4520,0xa0000},{0x5720,0xa0000},{0xd120,0xa0000},{0x143b0,0xa0000},{0x15430,0xa0000},{0x206c1,0xa0000},{0x21140,0xa0000},{0x40141,0xa0000},{0x301c0,0xa0000},{0x31140,0xa0000},{0x60641,0xa0000},{0x101c2,0xa0000},{0x40c40,0xa0000},{0x20143,0x600200},{0x71440,0xa0000},{0xe50043,0x10e0502},{0xe60023,0x10e0602},{0xe68023,0x10e0702},{0xe70023,0x10e0802},{0xe78013,0x10e0902},{0x70024,0x1000802},{0x78014,0x1000902},{0x5,0x0},{0x40044,0x1000402},{0x50044,0x1000502},{0x60024,0x1000602},{0x68024,0x1000702}},
    {{0x45a0,0xa0000},{0x57a0,0xa0000},{0xd1a0,0xa0000},{0x14430,0xa0000},{0x154b0,0xa0000},{0x20741,0xa0000},{0x211c0,0xa0000},{0x401c1,0xa0000},{0x30240,0xa0000},{0x311c0,0xa0000},{0x606c1,0xa0000},{0x10242,0xa0000},{0x40cc0,0xa0000},{0x201c3,0x600200},{0x714c0,0xa0000},{0xe500c3,0x10e0502},{0xe600a3,0x10e0602},{0xe680a3,0x10e0702},{0xe700a3,0x10e0802},{0xe78093,0x10e0902},{0x700a4,0x1000802},{0x78094,0x1000902},{0x5,0x0},{0x400c4,0x1000402},{0x500c4,0x1000502},{0x600a4,0x1000602},{0x680a4,0x1000702}},
    {{0x4620,0xa0000},{0xc020,0xa0000},{0xd220,0xa0000},{0x144b0,0xa0000},{0x15530,0xa0000},{0x20040,0xa0000},{0x21240,0xa0000},{0x40241,0xa0000},{0x302c0,0xa0000},{0x31240,0xa0000},{0x60741,0xa0000},{0x40040,0xa0000},{0x40d40,0xa0000},{0x20243,0x600200},{0x71540,0xa0000},{0xe50143,0x10e0502},{0xe60123,0x10e0602},{0xe68123,0x10e0702},{0xe70123,0x10e0802},{0xe78113,0x10e0902},{0x70124,0x1000802},{0x78114,0x1000902},{0x5,0x0},{0x40144,0x1000402},{0x50144,0x1000502},{0x60124,0x1000602},{0x68124,0x1000702}},
    {{0x46a0,0xa0000},{0xc0a0,0xa0000},{0xd2a0,0xa0000},{0x14530,0xa0000},{0x155b0,0xa0000},{0x200c0,0xa0000},{0x212c0,0xa0000},{0x402c1,0xa0000},{0x30340,0xa0000},{0x312c0,0xa0000},{0x42,0xa0000},{0x400c0,0xa0000},{0x40dc0,0xa0000},{0x20042,0xa0000},{0x50840,0xa0000},{0x512c0,0xa0000},{0x60040,0xa0000},{0x60ac0,0xa0000},{0x61540,0xa0000},{0xe401c3,0x10e0402},{0x700c0,0xa0000},{0x70dc0,0xa0000},{0xe501c3,0x10e0502},{0xe601a3,0x10e0602},{0x601a3,0x10e0600},{0xe681a3,0x10e0702},{0xe701a3,0x10e0802},{0xe78193,0x10e0902},{0x78194,0x1000902},{0x5,0x0},{0x401c4,0x1000402},{0x501c4,0x1000502},{0x601a4,0x1000602},{0x681a4,0x1000702}},
    {{0x4720,0xa0000},{0xc120,0xa0000},{0xd320,0xa0000},{0x145b0,0xa0000},{0x15630,0xa0000},{0x20140,0xa0000},{0x21340,0xa0000},{0x40341,0xa0000},{0x303c0,0xa0000},{0x31340,0xa0000},{0xc2,0xa0000},{0x40140,0xa0000},{0x40e40,0xa0000},{0x200c2,0xa0000},{0x508c0,0xa0000},{0x51340,0xa0000},{0x600c0,0xa0000},{0x60b40,0xa0000},{0x615c0,0xa0000},{0xe40243,0x10e0402},{0x70140,0xa0000},{0x70e40,0xa0000},{0xe50243,0x10e0502},{0xe60223,0x10e0602},{0x60223,0x10e0600},{0xe68223,0x10e0702},{0xe70223,0x10e0802},{0xe78213,0x10e0902},{0x78214,0x1000902},{0x5,0x0},{0x40244,0x1000402},{0x50244,0x1000502},{0x60224,0x1000602},{0x68224,0x1000702}},
    {{0x47a0,0xa0000},{0xc1a0,0xa0000},{0xd3a0,0xa0000},{0x14630,0xa0000},{0x156b0,0xa0000},{0x201c0,0xa0000},{0x213c0,0xa0000},{0x403c1,0xa0000},{0x30440,0xa0000},{0x313c0,0xa0000},{0x142,0xa0000},{0x401c0,0xa0000},{0x40ec0,0xa0000},{0x20142,0xa0000},{0x50940,0xa0000},{0x513c0,0xa0000},{0x60140,0xa0000},{0x60bc0,0xa0000},{0x61640,0xa0000},{0x1540043,0x10e0403},{0x701c0,0xa0000},{0x70ec0,0xa0000},{0x1550043,0x10e0503},{0x1560023,0x10e0603},{0x23600a3,0x10d0605},{0x1568023,0x10e0703},{0x1570023,0x10e0803},{0x1578013,0x10e0903},{0x70024,0x1000803},{0x78014,0x1000903},{0x5,0x0},{0x40044,0x1000403},{0x50044,0x1000503},{0x60024,0x1000603},{0x68024,0x1000703}},
    {{0x4820,0xa0000},{0xc220,0xa0000},{0xd420,0xa0000},{0x146b0,0xa0000},{0x15730,0xa0000},{0x20240,0xa0000},{0x21440,0xa0000},{0x40441,0xa0000},{0x304c0,0xa0000},{0x31440,0xa0000},{0x1c2,0xa0000},{0x40240,0xa0000},{0x40f40,0xa0000},{0x201c2,0xa0000},{0x509c0,0xa0000},{0x51440,0xa0000},{0x601c0,0xa0000},{0x60c40,0xa0000},{0x616c0,0xa0000},{0x15400c3,0x10e0403},{0x70240,0xa0000},{0x70f40,0xa0000},{0x15500c3,0x10e0503},{0x15600a3,0x10e0603},{0x2360123,0x10d0605},{0x15680a3,0x10e0703},{0x15700a3,0x10e0803},{0x1578093,0x10e0903},{0x700a4,0x1000803},{0x78094,0x1000903},{0x5,0x0},{0x400c4,0x1000403},{0x500c4,0x1000503},{0x600a4,0x1000603},{0x680a4,0x1000703}},
    {{0x48a0,0xa0000},{0xc2a0,0xa0000},{0xd4a0,0xa0000},{0x14730,0xa0000},{0x157b0,0xa0000},{0x202c0,0xa0000},{0x214c0,0xa0000},{0x404c1,0xa0000},{0x30540,0xa0000},{0x314c0,0xa0000},{0x242,0xa0000},{0x402c0,0xa0000},{0x40fc0,0xa0000},{0x20242,0xa0000},{0x50a40,0xa0000},{0x514c0,0xa0000},{0x60240,0xa0000},{0x60cc0,0xa0000},{0x61740,0xa0000},{0x1540143,0x10e0403},{0x702c0,0xa0000},{0x70fc0,0xa0000},{0x1550143,0x10e0503},{0x1560123,0x10e0603},{0x23601a3,0x10d0605},{0x1568123,0x10e0703},{0x1570123,0x10e0803},{0x1578113,0x10e0903},{0x70124,0x1000803},{0x78114,0x1000903},{0x5,0x0},{0x40144,0x1000403},{0x50144,0x1000503},{0x60124,0x1000603},{0x68124,0x1000703}},
    {{0x4920,0xa0000},{0xc320,0xa0000},{0xd520,0xa0000},{0x147b0,0xa0000},{0x10041,0xa0000},{0x20340,0xa0000},{0x21540,0xa0000},{0x40541,0xa0000},{0x305c0,0xa0000},{0x31540,0xa0000},{0x70041,0xa0000},{0x40340,0xa0000},{0x41040,0xa0000},{0x50040,0xa0000},{0x50ac0,0xa0000},{0x516c0,0xa0000},{0x60440,0xa0000},{0x60ec0,0xa0000},{0x50142,0xa0000},{0x15401c3,0x10e0403},{0x704c0,0xa0000},{0x711c0,0xa0000},{0x15501c3,0x10e0503},{0x15601a3,0x10e0603},{0x15681a3,0x10e0703},{0x15701a3,0x10e0803},{0x1578193,0x10e0903},{0x701a4,0x1000803},{0x78194,0x1000903},{0x5,0x0},{0x401c4,0x1000403},{0x501c4,0x1000503},{0x601a4,0x1000603},{0x681a4,0x1000703}},
    {{0x49a0,0xa0000},{0xc3a0,0xa0000},{0xd5a0,0xa0000},{0x14830,0xa0000},{0x100c1,0xa0000},{0x203c0,0xa0000},{0x215c0,0xa0000},{0x405c1,0xa0000},{0x30640,0xa0000},{0x315c0,0xa0000},{0x700c1,0xa0000},{0x403c0,0xa0000},{0x410c0,0xa0000},{0x500c0,0xa0000},{0x50b40,0xa0000},{0x51740,0xa0000},{0x604c0,0xa0000},{0x60f40,0xa0000},{0x501c2,0xa0000},{0x1540243,0x10e0403},{0x70540,0xa0000},{0x71240,0xa0000},{0x1550243,0x10e0503},{0x1560223,0x10e0603},{0x1568223,0x10e0703},{0x1570223,0x10e0803},{0x1578213,0x10e0903},{0x70224,0x1000803},{0x78214,0x1000903},{0x5,0x0},{0x40244,0x1000403},{0x50244,0x1000503},{0x60224,0x1000603},{0x68224,0x1000703}},
    {{0x4a20,0xa0000},{0xc420,0xa0000},{0xd620,0xa0000},{0x148b0,0xa0000},{0x10141,0xa0000},{0x20440,0xa0000},{0x21640,0xa0000},{0x40641,0xa0000},{0x306c0,0xa0000},{0x31640,0xa0000},{0x70141,0xa0000},{0x40440,0xa0000},{0x41140,0xa0000},{0x50140,0xa0000},{0x50bc0,0xa0000},{0x517c0,0xa0000},{0x60540,0xa0000},{0x60fc0,0xa0000},{0x50242,0xa0000},{0x1c40043,0x10e0404},{0x705c0,0xa0000},{0x712c0,0xa0000},{0x1c50043,0x10e0504},{0x1c60023,0x10e0604},{0x1c68023,0x10e0704},{0x1c70023,0x10e0804},{0x1c78013,0x10e0904},{0x70024,0x1000804},{0x78014,0x1000904},{0x5,0x0},{0x40044,0x1000404},{0x50044,0x1000504},{0x60024,0x1000604},{0x68024,0x1000704}},
    {{0x4aa0,0xa0000},{0xc4a0,0xa0000},{0xd6a0,0xa0000},{0x14930,0xa0000},{0x101c1,0xa0000},{0x204c0,0xa0000},{0x216c0,0xa0000},{0x406c1,0xa0000},{0x30740,0xa0000},{0x316c0,0xa0000},{0x701c1,0xa0000},{0x404c0,0xa0000},{0x411c0,0xa0000},{0x501c0,0xa0000},{0x50c40,0xa0000},{0x30042,0xa0000},{0x605c0,0xa0000},{0x61040,0xa0000},{0x1c400c3,0x10e0404},{0x29c00c3,0x10d0406},{0x706c0,0xa0000},{0x71640,0xa0000},{0x1c500c3,0x10e0504},{0x1c600a3,0x10e0604},{0x1c680a3,0x10e0704},{0x1c700a3,0x10e0804},{0x1c78093,0x10e0904},{0x700a4,0x1000804},{0x78094,0x1000904},{0x5,0x0},{0x400c4,0x1000404},{0x500c4,0x1000504},{0x600a4,0x1000604},{0x680a4,0x1000704}},
    {{0x4b20,0xa0000},{0xc520,0xa0000},{0xd720,0xa0000},{0x149b0,0xa0000},{0x10241,0xa0000},{0x20540,0xa0000},{0x21740,0xa0000},{0x40741,0xa0000},{0x307c0,0xa0000},{0x31740,0xa0000},{0x70241,0xa0000},{0x40540,0xa0000},{0x41240,0xa0000},{0x50240,0xa0000},{0x50cc0,0xa0000},{0x300c2,0xa0000},{0x60640,0xa0000},{0x610c0,0xa0000},{0x1c40143,0x10e0404},{0x29c0143,0x10d0406},{0x70740,0xa0000},{0x716c0,0xa0000},{0x1c50143,0x10e0504},{0x1c60123,0x10e0604},{0x1c68123,0x10e0704},{0x1c70123,0x10e0804},{0x1c78113,0x10e0904},{0x70124,0x1000804},{0x78114,0x1000904},{0x5,0x0},{0x40144,0x1000404},{0x50144,0x1000504},{0x60124,0x1000604},{0x68124,0x1000704}},
    {{0x4ba0,0xa0000},{0xc5a0,0xa0000},{0xd7a0,0xa0000},{0x14a30,0xa0000},{0x102c1,0xa0000},{0x205c0,0xa0000},{0x217c0,0xa0000},{0x50041,0xa0000},{0x30840,0xa0000},{0x317c0,0xa0000},{0x702c1,0xa0000},{0x405c0,0xa0000},{0x412c0,0xa0000},{0x502c0,0xa0000},{0x50d40,0xa0000},{0x30142,0xa0000},{0x606c0,0xa0000},{0x61140,0xa0000},{0x1c401c3,0x10e0404},{0x29c01c3,0x10d0406},{0x707c0,0xa0000},{0x71740,0xa0000},{0x1c501c3,0x10e0504},{0x1c601a3,0x10e0604},{0x1c681a3,0x10e0704},{0x1c701a3,0x10e0804},{0x1c78193,0x10e0904},{0x701a4,0x1000804},{0x78194,0x1000904},{0x5,0x0},{0x401c4,0x1000404},{0x501c4,0x1000504},{0x601a4,0x1000604},{0x681a4,0x1000704}},
    {{0x4c20,0xa0000},{0xc620,0xa0000},{0x41,0xa0000},{0x14ab0,0xa0000},{0x104c1,0xa0000},{0x207c0,0xa0000},{0x1c3,0x600000},{0x301c2,0xa0000},{0x60740,0xa0000},{0x611c0,0xa0000},{0x1c40243,0x10e0404},{0x60042,0xa0000},{0x70640,0xa0000},{0x715c0,0xa0000},{0x1c50243,0x10e0504},{0x1c60223,0x10e0604},{0x1c68223,0x10e0704},{0x1c70223,0x10e0804},{0x1c78213,0x10e0904},{0x70224,0x1000804},{0x78214,0x1000904},{0x5,0x0},{0x40244,0x1000404},{0x50244,0x1000504},{0x60224,0x1000604},{0x68224,0x1000704}},
    {{0x4ca0,0xa0000},{0xc6a0,0xa0000},{0xc1,0xa0000},{0x14b30,0xa0000},{0x10541,0xa0000},{0x20840,0xa0000},{0x243,0x600000},{0x30242,0xa0000},{0x607c0,0xa0000},{0x61240,0xa0000},{0x2340043,0x10d0405},{0x29c0243,0x10d0406},{0x70840,0xa0000},{0x717c0,0xa0000},{0x2350043,0x10d0505},{0x2360023,0x10d0605},{0x2368023,0x10d0705},{0x2370023,0x10d0805},{0x2378013,0x10d0905},{0x70024,0x1000805},{0x78014,0x1000905},{0x5,0x0},{0x40044,0x1000405},{0x50044,0x1000505},{0x60024,0x1000605},{0x68024,0x1000705}},
    {{0x4d20,0xa0000},{0xc720,0xa0000},{0x141,0xa0000},{0x14bb0,0xa0000},{0x105c1,0xa0000},{0x208c0,0xa0000},{0x30041,0xa0000},{0x500c1,0xa0000},{0x308c0,0xa0000},{0x10043,0x600100},{0x23400c3,0x10d0405},{0xe40043,0x10e0402},{0x708c0,0xa0000},{0x23500c3,0x10d0505},{0x29d00c3,0x10d0506},{0x23680a3,0x10d0705},{0x23700a3,0x10d0805},{0x2378093,0x10d0905},{0x700a4,0x1000805},{0x78094,0x1000905},{0x5,0x0},{0x400c4,0x1000405},{0x500c4,0x1000505},{0x600a4,0x1000605},{0x680a4,0x1000705}},
    {{0x4da0,0xa0000},{0xc7a0,0xa0000},{0x1c1,0xa0000},{0x14c30,0xa0000},{0x10641,0xa0000},{0x20940,0xa0000},{0x300c1,0xa0000},{0x50141,0xa0000},{0x30940,0xa0000},{0x100c3,0x600100},{0x2340143,0x10d0405},{0xe400c3,0x10e0402},{0x70940,0xa0000},{0x2350143,0x10d0505},{0x29d0143,0x10d0506},{0x2368123,0x10d0705},{0x2370123,0x10d0805},{0x2378113,0x10d0905},{0x70124,0x1000805},{0x78114,0x1000905},{0x5,0x0},{0x40144,0x1000405},{0x50144,0x1000505},{0x60124,0x1000605},{0x68124,0x1000705}},
    {{0x4e20,0xa0000},{0xc820,0xa0000},{0x241,0xa0000},{0x14cb0,0xa0000},{0x106c1,0xa0000},{0x209c0,0xa0000},{0x30141,0xa0000},{0x501c1,0xa0000},{0x309c0,0xa0000},{0x10143,0x600100},{0x23401c3,0x10d0405},{0xe40143,0x10e0402},{0x709c0,0xa0000},{0x23501c3,0x10d0505},{0x29d01c3,0x10d0506},{0x23681a3,0x10d0705},{0x23701a3,0x10d0805},{0x2378193,0x10d0905},{0x701a4,0x1000805},{0x78194,0x1000905},{0x5,0x0},{0x401c4,0x1000405},{0x501c4,0x1000505},{0x601a4,0x1000605},{0x681a4,0x1000705}},
    {{0x4ea0,0xa0000},{0xc8a0,0xa0000},{0x2c1,0xa0000},{0x14d30,0xa0000},{0x10741,0xa0000},{0x20a40,0xa0000},{0x301c1,0xa0000},{0x50241,0xa0000},{0x30a40,0xa0000},{0x101c3,0x600100},{0x2340243,0x10d0405},{0x7401c3,0x10e0401},{0x70a40,0xa0000},{0x2350243,0x10d0505},{0x29d0243,0x10d0506},{0x2368223,0x10d0705},{0x2370223,0x10d0805},{0x2378213,0x10d0905},{0x70224,0x1000805},{0x78214,0x1000905},{0x5,0x0},{0x40244,0x1000405},{0x50244,0x1000505},{0x60224,0x1000605},{0x68224,0x1000705}},
    {{0x4f20,0xa0000},{0xc920,0xa0000},{0x341,0xa0000},{0x14db0,0xa0000},{0x20041,0xa0000},{0x20ac0,0xa0000},{0x30241,0xa0000},{0x502c1,0xa0000},{0x30ac0,0xa0000},{0x10243,0x600100},{0x29c0043,0x10d0406},{0x740243,0x10e0401},{0x70ac0,0xa0000},{0x29d0043,0x10d0506},{0x70042,0xa0000},{0x29e0023,0x10d0606},{0x29e8023,0x10d0706},{0x29f0023,0x10d0806},{0x29f8013,0x10d0906},{0x70024,0x1000806},{0x78014,0x1000906},{0x5,0x0},{0x40044,0x1000406},{0x50044,0x1000506},{0x60024,0x1000606},{0x68024,0x1000706}},
    {{0x4fa0,0xa0000},{0xc9a0,0xa0000},{0x3c1,0xa0000},{0x14e30,0xa0000},{0x200c1,0xa0000},{0x20b40,0xa0000},{0x302c1,0xa0000},{0x50341,0xa0000},{0x30b40,0xa0000},{0x60041,0xa0000},{0x70341,0xa0000},{0x40640,0xa0000},{0x41340,0xa0000},{0x50340,0xa0000},{0x50dc0,0xa0000},{0x30043,0x600300},{0x29e00a3,0x10d0606},{0x29e80a3,0x10d0706},{0x29f00a3,0x10d0806},{0x29f8093,0x10d0906},{0x700a4,0x1000806},{0x78094,0x1000906},{0x5,0x0},{0x400c4,0x1000406},{0x500c4,0x1000506},{0x600a4,0x1000606},{0x680a4,0x1000706}},
    {{0x5020,0xa0000},{0xca20,0xa0000},{0x441,0xa0000},{0x14eb0,0xa0000},{0x20141,0xa0000},{0x20bc0,0xa0000},{0x30341,0xa0000},{0x503c1,0xa0000},{0x30bc0,0xa0000},{0x600c1,0xa0000},{0x703c1,0xa0000},{0x406c0,0xa0000},{0x413c0,0xa0000},{0x503c0,0xa0000},{0x50e40,0xa0000},{0x300c3,0x600300},{0x29e0123,0x10d0606},{0x29e8123,0x10d0706},{0x29f0123,0x10d0806},{0x29f8113,0x10d0906},{0x70124,0x1000806},{0x78114,0x1000906},{0x5,0x0},{0x40144,0x1000406},{0x50144,0x1000506},{0x60124,0x1000606},{0x68124,0x1000706}},
    {{0x50a0,0xa0000},{0xcaa0,0xa0000},{0x4c1,0xa0000},{0x14f30,0xa0000},{0x201c1,0xa0000},{0x20c40,0xa0000},{0x303c1,0xa0000},{0x50441,0xa0000},{0x30c40,0xa0000},{0x60141,0xa0000},{0x70441,0xa0000},{0x40740,0xa0000},{0x41440,0xa0000},{0x50440,0xa0000},{0x50ec0,0xa0000},{0x30143,0x600300},{0x29e01a3,0x10d0606},{0x29e81a3,0x10d0706},{0x29f01a3,0x10d0806},{0x29f8193,0x10d0906},{0x701a4,0x1000806},{0x78194,0x1000906},{0x5,0x0},{0x401c4,0x1000406},{0x501c4,0x1000506},{0x601a4,0x1000606},{0x681a4,0x1000706}},
    {{0x5120,0xa0000},{0xcb20,0xa0000},{0x541,0xa0000},{0x14fb0,0xa0000},{0x20241,0xa0000},{0x20cc0,0xa0000},{0x30441,0xa0000},{0x504c1,0xa0000},{0x30cc0,0xa0000},{0x601c1,0xa0000},{0x704c1,0xa0000},{0x407c0,0xa0000},{0x414c0,0xa0000},{0x504c0,0xa0000},{0x50f40,0xa0000},{0x301c3,0x600300},{0x29e0223,0x10d0606},{0x29e8223,0x10d0706},{0x29f0223,0x10d0806},{0x29f8213,0x10d0906},{0x70224,0x1000806},{0x78214,0x1000906},{0x5,0x0},{0x40244,0x1000406},{0x50244,0x1000506},{0x60224,0x1000606},{0x68224,0x1000706}},
    {{0x51a0,0xa0000},{0xcba0,0xa0000},{0x5c1,0xa0000},{0x15030,0xa0000},{0x202c1,0xa0000},{0x20d40,0xa0000},{0x304c1,0xa0000},{0x50541,0xa0000},{0x30d40,0xa0000},{0x60241,0xa0000},{0x70541,0xa0000},{0x40840,0xa0000},{0x41540,0xa0000},{0x50540,0xa0000},{0x50fc0,0xa0000},{0x30243,0x600300},{0x760023,0x10e0601},{0x68023,0x10e0700},{0x70124,0x1000801},{0x701a4,0x1000802},{0x78014,0x1000900},{0x5,0x0}},
}};
#define D8(i) "+f"(d[i]), "+f"(d[i + 1]), "+f"(d[i + 2]), "+f"(d[i + 3]), "+f"(d[i + 4]), "+f"(d[i + 5]), "+f"(d[i + 6]), "+f"(d[i + 7])
template <int N> __device__ __forceinline__ void wgmma_side(float* d, uint32_t alo, uint32_t blo, int sc);
template <> __device__ __forceinline__ void wgmma_side<64>(float* d, uint32_t alo, uint32_t blo, int sc) {
    asm volatile("{.reg .pred p; .reg .b64 ad, bd; setp.ne.b32 p, %34, 0; mov.b64 ad, {%32, 0x40000040}; mov.b64 bd, {%33, 0x40000040};\n"
                 "wgmma.mma_async.sync.aligned.m64n64k16.f32.bf16.bf16 "
                 "{%0,%1,%2,%3,%4,%5,%6,%7,%8,%9,%10,%11,%12,%13,%14,%15,%16,%17,%18,%19,%20,%21,%22,%23,%24,%25,%26,%27,%28,%29,%30,%31},"
                 " ad, bd, p, 1, 1, 1, 0;}"
                 : D8(0), D8(8), D8(16), D8(24)
                 : "r"(alo), "r"(blo), "r"(sc));
}
template <> __device__ __forceinline__ void wgmma_side<128>(float* d, uint32_t alo, uint32_t blo, int sc) {
    asm volatile("{.reg .pred p; .reg .b64 ad, bd; setp.ne.b32 p, %66, 0; mov.b64 ad, {%64, 0x40000040}; mov.b64 bd, {%65, 0x40000040};\n"
                 "wgmma.mma_async.sync.aligned.m64n128k16.f32.bf16.bf16 "
                 "{%0,%1,%2,%3,%4,%5,%6,%7,%8,%9,%10,%11,%12,%13,%14,%15,%16,%17,%18,%19,%20,%21,%22,%23,%24,%25,%26,%27,%28,%29,%30,%31,"
                 "%32,%33,%34,%35,%36,%37,%38,%39,%40,%41,%42,%43,%44,%45,%46,%47,%48,%49,%50,%51,%52,%53,%54,%55,%56,%57,%58,%59,%60,%61,%62,%63},"
                 " ad, bd, p, 1, 1, 1, 0;}"
                 : D8(0), D8(8), D8(16), D8(24), D8(32), D8(40), D8(48), D8(56)
                 : "r"(alo), "r"(blo), "r"(sc));
}
template <> __device__ __forceinline__ void wgmma_side<192>(float* d, uint32_t alo, uint32_t blo, int sc) {
    asm volatile("{.reg .pred p; .reg .b64 ad, bd; setp.ne.b32 p, %98, 0; mov.b64 ad, {%96, 0x40000040}; mov.b64 bd, {%97, 0x40000040};\n"
                 "wgmma.mma_async.sync.aligned.m64n192k16.f32.bf16.bf16 "
                 "{%0,%1,%2,%3,%4,%5,%6,%7,%8,%9,%10,%11,%12,%13,%14,%15,%16,%17,%18,%19,%20,%21,%22,%23,%24,%25,%26,%27,%28,%29,%30,%31,"
                 "%32,%33,%34,%35,%36,%37,%38,%39,%40,%41,%42,%43,%44,%45,%46,%47,%48,%49,%50,%51,%52,%53,%54,%55,%56,%57,%58,%59,%60,%61,%62,%63,"
                 "%64,%65,%66,%67,%68,%69,%70,%71,%72,%73,%74,%75,%76,%77,%78,%79,%80,%81,%82,%83,%84,%85,%86,%87,%88,%89,%90,%91,%92,%93,%94,%95},"
                 " ad, bd, p, 1, 1, 1, 0;}"
                 : D8(0), D8(8), D8(16), D8(24), D8(32), D8(40), D8(48), D8(56), D8(64), D8(72), D8(80), D8(88)
                 : "r"(alo), "r"(blo), "r"(sc));
}
template <> __device__ __forceinline__ void wgmma_side<256>(float* d, uint32_t alo, uint32_t blo, int sc) {
    asm volatile("{.reg .pred p; .reg .b64 ad, bd; setp.ne.b32 p, %130, 0; mov.b64 ad, {%128, 0x40000040}; mov.b64 bd, {%129, 0x40000040};\n"
                 "wgmma.mma_async.sync.aligned.m64n256k16.f32.bf16.bf16 "
                 "{%0,%1,%2,%3,%4,%5,%6,%7,%8,%9,%10,%11,%12,%13,%14,%15,%16,%17,%18,%19,%20,%21,%22,%23,%24,%25,%26,%27,%28,%29,%30,%31,"
                 "%32,%33,%34,%35,%36,%37,%38,%39,%40,%41,%42,%43,%44,%45,%46,%47,%48,%49,%50,%51,%52,%53,%54,%55,%56,%57,%58,%59,%60,%61,%62,%63,"
                 "%64,%65,%66,%67,%68,%69,%70,%71,%72,%73,%74,%75,%76,%77,%78,%79,%80,%81,%82,%83,%84,%85,%86,%87,%88,%89,%90,%91,%92,%93,%94,%95,"
                 "%96,%97,%98,%99,%100,%101,%102,%103,%104,%105,%106,%107,%108,%109,%110,%111,%112,%113,%114,%115,%116,%117,%118,%119,%120,%121,%122,%123,%124,%125,%126,%127},"
                 " ad, bd, p, 1, 1, 1, 0;}"
                 : D8(0), D8(8), D8(16), D8(24), D8(32), D8(40), D8(48), D8(56), D8(64), D8(72), D8(80), D8(88), D8(96), D8(104), D8(112), D8(120)
                 : "r"(alo), "r"(blo), "r"(sc));
}
#define W8(i) "=f"(d[i]), "=f"(d[i + 1]), "=f"(d[i + 2]), "=f"(d[i + 3]), "=f"(d[i + 4]), "=f"(d[i + 5]), "=f"(d[i + 6]), "=f"(d[i + 7])
__device__ __forceinline__ void wgmma_first(float* d, uint32_t alo, uint32_t blo) {
    asm volatile("{.reg .pred p; .reg .b64 ad, bd; setp.ne.b32 p, %130, 0; mov.b64 ad, {%128, 0x40000040}; mov.b64 bd, {%129, 0x40000040};\n"
                 "wgmma.mma_async.sync.aligned.m64n256k16.f32.bf16.bf16 "
                 "{%0,%1,%2,%3,%4,%5,%6,%7,%8,%9,%10,%11,%12,%13,%14,%15,%16,%17,%18,%19,%20,%21,%22,%23,%24,%25,%26,%27,%28,%29,%30,%31,"
                 "%32,%33,%34,%35,%36,%37,%38,%39,%40,%41,%42,%43,%44,%45,%46,%47,%48,%49,%50,%51,%52,%53,%54,%55,%56,%57,%58,%59,%60,%61,%62,%63,"
                 "%64,%65,%66,%67,%68,%69,%70,%71,%72,%73,%74,%75,%76,%77,%78,%79,%80,%81,%82,%83,%84,%85,%86,%87,%88,%89,%90,%91,%92,%93,%94,%95,"
                 "%96,%97,%98,%99,%100,%101,%102,%103,%104,%105,%106,%107,%108,%109,%110,%111,%112,%113,%114,%115,%116,%117,%118,%119,%120,%121,%122,%123,%124,%125,%126,%127},"
                 " ad, bd, p, 1, 1, 1, 0;}"
                 : W8(0), W8(8), W8(16), W8(24), W8(32), W8(40), W8(48), W8(56), W8(64), W8(72), W8(80), W8(88), W8(96), W8(104), W8(112), W8(120)
                 : "r"(alo), "r"(blo), "n"(0));
}
#undef W8
#undef D8

__device__ __forceinline__ void bulk_st(void* dst, uint32_t src, uint32_t bytes) {
    asm volatile("cp.async.bulk.global.shared::cta.bulk_group [%0], [%1], %2;" :: "l"(dst), "r"(src), "r"(bytes) : "memory");
}
__device__ __forceinline__ void red_release(uint32_t* p, uint32_t v) { asm volatile("red.release.gpu.global.add.u32 [%0], %1;" :: "l"(p), "r"(v) : "memory"); }
__device__ __forceinline__ void wait_ge(const uint32_t* p, uint32_t v) { for (int c = 0; c < SPIN_LIM && (int)(ld_acquire(p) - v) < 0; c++) { } }
__device__ __forceinline__ uint4* part_ptr(Job job, int wg) {
    return g_op + (size_t)((job.x >> 13) & 63) * (10 * NKS * 256) + (((job.x >> 7) & 63) * 2 + wg) * NKS * ((job.x >> 3) & 15) * 256;
}

template <int T>
__device__ __forceinline__ void side_job(Job job, uint32_t& it, uint32_t& n, uint32_t sb, uint32_t sa, int wg, int t)
{
    float acc[T / 2];
    const int nkb = job.y >> 16 & 255;
    constexpr uint32_t NS = T == 64 ? 2 * SST : SST, SZ = SST * S_STAGE / NS, BO = T == 64 ? SB_FINE : 0;
    constexpr bool peel = T == 256;
    uint32_t prev = 0;
    auto block = [&](int kb, auto FIRST) {
        const uint32_t st = it % NS;
        const uint32_t alo = ((sb + st * SZ + wg * 8192) >> 4) | (64u << 16), blo = ((sb + st * SZ + 16384) >> 4) | (1u << 16);
        mbar_wait_long(sb + SB_FULL + BO + 8 * st, (it / NS) & 1);
        wg_fence();
        if constexpr (FIRST.value) wgmma_first(acc, alo, blo);
#pragma unroll
        for (int k4 = FIRST.value; k4 < 4; k4++) wgmma_side<T>(acc, alo + k4 * 128, blo + k4 * 2, peel ? 1 : kb | k4);
        wg_commit();
        if (peel ? !FIRST.value : kb) { wg_wait<1>(); arrive_e(prev); }
        prev = sb + SB_EMPTY + BO + 8 * st;
        it++;
    };
    if constexpr (peel) block(0, IC<1>());
    else {
#pragma unroll
        for (int i = 0; i < T / 2; i++) acc[i] = 0.f;
    }
    for (int kb = peel; kb < nkb; kb++) block(kb, IC<0>());
    if (n) mbar_wait_long(sb + SB_FREE, (n - 1) & 1);
    n++;
    wg_wait<0>();
    arrive_e(prev);
    const bool raw = (job.x & 7) == JV || job.y >> 24;
#pragma unroll
    for (int u = 0; u < T / 16; u++) {
        const uint4 w = make_uint4(pack2(acc[8 * u], acc[8 * u + 1]), pack2(acc[8 * u + 2], acc[8 * u + 3]),
                                   pack2(acc[8 * u + 4], acc[8 * u + 5]), pack2(acc[8 * u + 6], acc[8 * u + 7]));
        if (raw || T != 256) sts4(sb + S_STG + wg * 32768 + t * 16 + u * 2048, make_uint4(w.x, w.z, w.y, w.w));
        else stsm4t(sb + S_STG + wg * 32768 + sa + u * 2048, w.x, w.y, w.z, w.w);
    }
    __syncwarp();
    arrive_e(sb + SB_STAGED + 8 * wg);
}

__device__ __forceinline__ void ld20(const bf16* p, uint32_t* w) {
#pragma unroll
    for (int i = 0; i < 5; i++) asm volatile("ld.global.v2.b32 {%0,%1}, [%2];" : "=r"(w[2 * i]), "=r"(w[2 * i + 1]) : "l"(p + 4 * i) : "memory");
}

__global__ void __launch_bounds__(384, 1) side_kernel(const __grid_constant__ SideParams P)
{
    extern __shared__ __align__(1024) uint8_t smem[];
    const uint32_t sb = smem_u32(smem);
    const int tid = threadIdx.x, lane = tid & 31;
    const int warp = __shfl_sync(0xffffffffu, tid >> 5, 0);
    if (tid == 0) {
        for (int i = 0; i < SST; i++) { mbar_init(sb + SB_FULL + 8 * i, 1); mbar_init(sb + SB_EMPTY + 8 * i, 8); }
        for (int i = 0; i < 2 * SST; i++) { mbar_init(sb + SB_FULL + SB_FINE + 8 * i, 1); mbar_init(sb + SB_EMPTY + SB_FINE + 8 * i, 8); }
        mbar_init(sb + SB_STAGED, 4); mbar_init(sb + SB_STAGED + 8, 4); mbar_init(sb + SB_FREE, 1);
        asm volatile("fence.mbarrier_init.release.cluster;" ::: "memory");
    }
    __syncthreads();
    const Job* jobs = c_jobs.j[blockIdx.x];
    if (warp < 8) {
        asm volatile("setmaxnreg.inc.sync.aligned.u32 192;");
        const uint32_t ep = ld_epoch();
        uint32_t it = 0, it2 = 0, n = 0;
        const int wg = warp >> 2, t = tid & 127;
        const uint32_t sa = ((lane & 7) + ((lane >> 4) << 3)) * 128 + (((2 * (t >> 5) + ((lane >> 3) & 1)) ^ (lane & 7)) << 4);
        for (int j = 0; ; j++) {
            const Job job = jobs[j];
            const int type = job.x & 7, nb = (job.x >> 3) & 15;
            if (type == JEND) break;
            if (type == JR) {
                const int ks = job.y & 15, ct = (job.x >> 7) & 63;
                if (t == 0) {
                    asm volatile("cp.async.bulk.wait_group.read 0;" ::: "memory");
                    wait_ge(g_cnt + CNT_O + (job.y >> 8 & 255) * 5 + ct, ep * NKS);
                }
                bar_sync(1 + wg, 128);
                const uint4* part = part_ptr(job, wg) + ks * 128 + t;
                const uint32_t rs = sb + S_RST + wg * 6144;
                uint4 q[3][NKS];
#pragma unroll
                for (int i = 0; i < 3; i++) {
#pragma unroll
                    for (int k = 0; k < NKS; k++) q[i][k] = make_uint4(0, 0, 0, 0);
                    if (ks + i * NKS < 2 * nb) {
#pragma unroll
                        for (int k = 0; k < NKS; k++) q[i][k] = ld_pkt(part + k * nb * 256 + i * NKS * 128);
                    }
                }
#pragma unroll
                for (int i = 0; i < 3; i++)
                    if (ks + i * NKS < 2 * nb) {
                        float r[8] = {0, 0, 0, 0, 0, 0, 0, 0};
#pragma unroll
                        for (int k = 0; k < NKS; k++) {
                            r[0] += bf_lo(q[i][k].x); r[1] += bf_hi(q[i][k].x); r[2] += bf_lo(q[i][k].y); r[3] += bf_hi(q[i][k].y);
                            r[4] += bf_lo(q[i][k].z); r[5] += bf_hi(q[i][k].z); r[6] += bf_lo(q[i][k].w); r[7] += bf_hi(q[i][k].w);
                        }
                        stsm4t(rs + sa + i * 2048, pack2(r[0], r[1]), pack2(r[4], r[5]), pack2(r[2], r[3]), pack2(r[6], r[7]));
                    }
                asm volatile("fence.proxy.async.shared::cta;" ::: "memory");
                bar_sync(1 + wg, 128);
                if (t == 0) {
                    for (int i = 0; i < 3; i++)
                        if (ks + i * NKS < 2 * nb) tma_st(&P.sto, rs + i * 2048, DM + ct * 128 + wg * 64, ((job.x >> 13) & 63) * 32 + (ks + i * NKS) * 16);
                    asm volatile("cp.async.bulk.commit_group;" ::: "memory");
                }
                __syncwarp();
                continue;
            }
            switch (nb) {
                case 8: side_job<256>(job, it, n, sb, sa, wg, t); break;
                case 6: side_job<192>(job, it, n, sb, sa, wg, t); break;
                case 4: side_job<128>(job, it, n, sb, sa, wg, t); break;
                default: side_job<64>(job, it2, n, sb, sa, wg, t); break;
            }
        }
        if (t == 0) asm volatile("cp.async.bulk.wait_group 0;" ::: "memory");
    } else {
        asm volatile("setmaxnreg.dec.sync.aligned.u32 120;");
        if (warp == 8) {
            uint32_t ep = 0, ns = SST, sz = S_STAGE, bo = sb, sa = 0, pa = 1, sl = 0;
            for (int j = 0; ; j++) {
                const Job job = jobs[j];
                const int type = job.x & 7;
                if (type == JEND) break;
                if (type == JR) continue;
                const int nb = (job.x >> 3) & 15, c0 = ((job.x >> 7) & 63) * 2, seg0 = (job.x >> 13) & 63, kb0 = (job.x >> 19) & 127,
                          nkb = job.y >> 16 & 255;
                const CUtensorMap *ta = &P.a[type], *tb = nb == 8 ? &P.b[type] : &P.c[(type == JV ? 3 : 4) - nb / 2];
                auto ready = [&]() {
                    bool ok = true;
                    if (type == JP) ok = (int)(ld_acquire(g_cnt + CNT_ATT + (seg0 >> 3)) - ep * 256) >= 0;
                    else
                        for (int i = 0; i < nkb; i += 32) ok &= (int)(ld_acquire(g_prog + kb0 + min(i + lane, nkb - 1)) - (ep * 128 + seg0 + nb)) >= 0;
                    return __all_sync(0xffffffffu, ok);
                };
                if (nb == 2 && ns == SST) {
                    for (uint32_t i = 0; i < SST; i++) mbar_wait_long(sb + SB_EMPTY + 8 * i, pa ^ (i < sa));
                    ns = 2 * SST; sz = S_STAGE / 2; bo = sb + SB_FINE; sa = 0; pa = 1; sl = 0;
                }
                auto loadA = [&](int kb) {
                    const uint32_t full = bo + SB_FULL + 8 * sa;
                    mbar_wait_long(bo + SB_EMPTY + 8 * sa, pa);
                    expect_e(full, 16384 + nb * 4096);
                    tma3d_e(sb + sa * sz, ta, (kb0 + kb) * 64, c0, full);
                    if (++sa == ns) { sa = 0; pa ^= 1; }
                };
                auto loadB = [&](int kb) {
                    tma2d_e(sb + sl * sz + 16384, tb, (kb0 + kb) * 64, seg0 * 32, bo + SB_FULL + 8 * sl);
                    if (++sl == ns) sl = 0;
                };
                int pre = 0;
                if (type >= JP) {
                    if (!ready()) {
                        pre = ns;
#pragma unroll 1
                        for (int kb = 0; kb < pre; kb++) loadA(kb);
                        for (int c = 0; c < SPIN_LIM && !ready(); c++) { }
                    }
                    asm volatile("fence.proxy.async.global;" ::: "memory");
                }
#pragma unroll 1
                for (int kb = 0; kb < nkb; kb++) { if (kb >= pre) loadA(kb); loadB(kb); }
                if (j == 0) ep = ld_epoch();
            }
            if (blockIdx.x == 0 && lane == 0) g_epoch = ep;
        } else if (warp == 9) {
            if (lane == 0) {
                const uint32_t ep = ld_epoch();
                uint32_t n = 0;
                for (int j = 0; ; j++) {
                    const Job job = jobs[j];
                    const int type = job.x & 7;
                    if (type == JEND) break;
                    if (type == JR) continue;
                    const int nb = (job.x >> 3) & 15, ct = (job.x >> 7) & 63, seg0 = (job.x >> 13) & 63;
                    for (int wg = 0; wg < 2; wg++) {
                        const uint32_t src = sb + S_STG + wg * 32768;
                        mbar_wait_long(sb + SB_STAGED + 8 * wg, n & 1);
                        asm volatile("fence.proxy.async.shared::cta;" ::: "memory");
                        if (type == JV) bulk_st(g_vx + ((ct * 2 + wg) * 64 + seg0) * 256, src, nb * 4096);
                        else if (job.y >> 24) bulk_st(part_ptr(job, wg) + (job.y & 15) * nb * 256, src, nb * 4096);
                        else tma_st(&P.st[type != JQ], src, (type == JO ? DM : 0) + ct * 128 + wg * 64, seg0 * 32);
                    }
                    asm volatile("cp.async.bulk.commit_group;" ::: "memory");
                    asm volatile("cp.async.bulk.wait_group.read 0;" ::: "memory");
                    mbar_arrive(sb + SB_FREE);
                    asm volatile("cp.async.bulk.wait_group 0;" ::: "memory");
                    if (type == JV) { st_release(g_flagv + ct * 128 + seg0, ep); g_flagv[ct * 128 + 64 + seg0] = ep; }
                    if (type == JQ) red_release(g_cnt + CNT_Q + (seg0 >> 3), 1);
                    if (job.y >> 24) red_release(g_cnt + CNT_O + (job.y >> 8 & 255) * 5 + ct, 1);
                    n++;
                }
            }
        } else {
            const uint32_t ep = ld_epoch();
            const float scl = 0.22360679774997896f * 1.4426950408889634f;
            for (int p = blockIdx.x * 2 + warp - 10; p < SEQ / 2; p += 2 * NSIDE) {
                const int t0 = 4 * (p >> 1) + (p & 1);
                wait_ge(g_cnt + CNT_Q + (max(t0 - 14, 0) >> 8), ep * 15);
                wait_ge(g_cnt + CNT_Q + (t0 >> 8), ep * 15);
                const bf16* base = g_qkvA + lane * 20;
                uint32_t w[18][10];
                auto row = [&](int j) { if (j < 18) ld20(base + (size_t)max(t0 + 2 - 2 * (j % 9), 0) * 1920 + (j < 9 ? 640 : 1280), w[j]); };
                float l0[8], l1[8];
                {
                    uint32_t u0[10], u1[10];
                    float q0[20], q1[20];
                    ld20(base + (size_t)t0 * 1920, u0); ld20(base + (size_t)(t0 + 2) * 1920, u1);
                    row(0); row(1);
#pragma unroll
                    for (int i = 0; i < 10; i++) { q0[2 * i] = bf_lo(u0[i]); q0[2 * i + 1] = bf_hi(u0[i]); q1[2 * i] = bf_lo(u1[i]); q1[2 * i + 1] = bf_hi(u1[i]); }
#pragma unroll
                    for (int j = 0; j < 9; j++) {
                        row(j + 2);
                        blk(warp);
                        float a0 = 0.f, a1 = 0.f;
#pragma unroll
                        for (int i = 0; i < 10; i++) {
                            const float lo = bf_lo(w[j][i]), hi = bf_hi(w[j][i]);
                            if (j > 0) a0 = fmaf(q0[2 * i + 1], hi, fmaf(q0[2 * i], lo, a0));
                            if (j < 8) a1 = fmaf(q1[2 * i + 1], hi, fmaf(q1[2 * i], lo, a1));
                        }
                        const bool in = t0 + 2 - 2 * j >= 0;
                        if (j > 0) l0[j - 1] = in ? a0 * scl : -3.0e38f;
                        if (j < 8) l1[j] = in ? a1 * scl : -3.0e38f;
                    }
                }
                float m0 = l0[0], m1 = l1[0], s0 = 0.f, s1 = 0.f;
#pragma unroll
                for (int j = 1; j < 8; j++) { m0 = fmaxf(m0, l0[j]); m1 = fmaxf(m1, l1[j]); }
#pragma unroll
                for (int j = 0; j < 8; j++) { l0[j] = ex2(l0[j] - m0); s0 += l0[j]; l1[j] = ex2(l1[j] - m1); s1 += l1[j]; }
                float o0[20], o1[20];
#pragma unroll
                for (int i = 0; i < 20; i++) o0[i] = o1[i] = 0.f;
#pragma unroll
                for (int j = 0; j < 9; j++) {
                    row(j + 11);
                    blk(warp);
#pragma unroll
                    for (int i = 0; i < 10; i++) {
                        const float lo = bf_lo(w[9 + j][i]), hi = bf_hi(w[9 + j][i]);
                        if (j > 0) { o0[2 * i] = fmaf(l0[j - 1], lo, o0[2 * i]); o0[2 * i + 1] = fmaf(l0[j - 1], hi, o0[2 * i + 1]); }
                        if (j < 8) { o1[2 * i] = fmaf(l1[j], lo, o1[2 * i]); o1[2 * i + 1] = fmaf(l1[j], hi, o1[2 * i + 1]); }
                    }
                }
                s0 = 1.f / s0; s1 = 1.f / s1;
                uint2* dst = reinterpret_cast<uint2*>(g_oA + (size_t)t0 * DM + lane * 20);
#pragma unroll
                for (int i = 0; i < 5; i++) {
                    dst[i] = make_uint2(pack2(o0[4 * i] * s0, o0[4 * i + 1] * s0), pack2(o0[4 * i + 2] * s0, o0[4 * i + 3] * s0));
                    dst[i + 2 * DM / 4] = make_uint2(pack2(o1[4 * i] * s1, o1[4 * i + 1] * s1), pack2(o1[4 * i + 2] * s1, o1[4 * i + 3] * s1));
                }
                __syncwarp();
                if (lane == 0) red_release(g_cnt + CNT_ATT + (t0 >> 8), 2);
            }
            int j = 0;
            while ((jobs[j].x & 7) != JEND) j++;
            for (j++; (jobs[j].x & 7) == JR; j++) {
                const Job job = jobs[j];
                const int nb = (job.x >> 3) & 15, ct = (job.x >> 7) & 63;
                for (int c = 0; c < SPIN_LIM && (int)(ld_acquire(g_cnt + CNT_O + (job.y >> 8 & 255) * 5 + ct) - ep * NKS) < 0; c++) __nanosleep(200);
                for (int u = job.y & 15; u < 2 * nb; u += NKS) {
                    const uint4* part = part_ptr(job, warp - 10) + u * 128 + lane;
                    bf16* op = P.out + (size_t)(((job.x >> 13) & 63) * 32 + u * 16 + (lane >> 2)) * OUTW + DM + ct * 128 + (warp - 10) * 64 + (lane & 1) * 8 + (lane & 2) * 2;
#pragma unroll 1
                    for (int h = 0; h < 2; h++) {
                        uint4 q[2][NKS];
#pragma unroll
                        for (int i = 0; i < 2; i++)
#pragma unroll
                            for (int k = 0; k < NKS; k++) q[i][k] = ld_pkt(part + k * nb * 256 + (2 * h + i) * 32);
#pragma unroll
                        for (int i = 0; i < 2; i++) {
                            float r[8] = {0, 0, 0, 0, 0, 0, 0, 0};
#pragma unroll
                            for (int k = 0; k < NKS; k++) {
                                r[0] += bf_lo(q[i][k].x); r[1] += bf_hi(q[i][k].x); r[2] += bf_lo(q[i][k].y); r[3] += bf_hi(q[i][k].y);
                                r[4] += bf_lo(q[i][k].z); r[5] += bf_hi(q[i][k].z); r[6] += bf_lo(q[i][k].w); r[7] += bf_hi(q[i][k].w);
                            }
#pragma unroll
                            for (int m = 0; m < 2; m++) {
                                const uint32_t a = movm(pack2(r[2 * m], r[2 * m + 1])), b = movm(pack2(r[4 + 2 * m], r[5 + 2 * m]));
                                const uint32_t o = __shfl_xor_sync(0xffffffffu, lane & 1 ? a : b, 1);
                                *reinterpret_cast<uint2*>(op + m * 8 * OUTW + (2 * h + i) * 16) = lane & 1 ? make_uint2(o, b) : make_uint2(a, o);
                            }
                        }
                    }
                }
            }
        }
    }
}

typedef CUresult (*EncodeFn)(CUtensorMap*, CUtensorMapDataType, cuuint32_t, void*, const cuuint64_t*, const cuuint64_t*,
                             const cuuint32_t*, const cuuint32_t*, CUtensorMapInterleave, CUtensorMapSwizzle,
                             CUtensorMapL2promotion, CUtensorMapFloatOOBfill);
static void make_map(EncodeFn enc, CUtensorMap* tm, const void* ptr, uint64_t cols, uint64_t rows, uint32_t bc, uint32_t br) {
    cuuint64_t dims[2] = {cols, rows}, strides[1] = {cols * 2};
    cuuint32_t box[2] = {bc, br}, es[2] = {1, 1};
    enc(tm, CU_TENSOR_MAP_DATA_TYPE_BFLOAT16, 2, const_cast<void*>(ptr), dims, strides, box, es, CU_TENSOR_MAP_INTERLEAVE_NONE,
        bc == 64 ? CU_TENSOR_MAP_SWIZZLE_128B : CU_TENSOR_MAP_SWIZZLE_64B,
        CU_TENSOR_MAP_L2_PROMOTION_L2_128B, CU_TENSOR_MAP_FLOAT_OOB_FILL_NONE);
}

static void make_map3(EncodeFn enc, CUtensorMap* tm, const void* ptr, uint64_t cols, uint64_t rows, uint32_t br, uint32_t nb, uint32_t bc = 64) {
    cuuint64_t dims[3] = {bc, rows, cols / bc}, strides[2] = {cols * 2, bc * 2};
    cuuint32_t box[3] = {bc, br, nb}, es[3] = {1, 1, 1};
    enc(tm, CU_TENSOR_MAP_DATA_TYPE_BFLOAT16, 3, const_cast<void*>(ptr), dims, strides, box, es, CU_TENSOR_MAP_INTERLEAVE_NONE,
        bc == 64 ? CU_TENSOR_MAP_SWIZZLE_128B : CU_TENSOR_MAP_SWIZZLE_64B,
        CU_TENSOR_MAP_L2_PROMOTION_L2_128B, CU_TENSOR_MAP_FLOAT_OOB_FILL_NONE);
}

extern "C" void kernel_launch(void* const* d_in, const int* in_sizes, int n_in, void* d_out, int out_size) {
    (void)in_sizes; (void)n_in; (void)out_size;
    const bf16* A_x = (const bf16*)d_in[0];
    const bf16* A_wqkv = (const bf16*)d_in[1];
    const bf16* A_wo = (const bf16*)d_in[2];
    const bf16* B_x = (const bf16*)d_in[3];
    const bf16* B_mem0 = (const bf16*)d_in[4];
    const bf16* B_Wq = (const bf16*)d_in[5];
    const bf16* B_Wk = (const bf16*)d_in[6];
    const bf16* B_Wv = (const bf16*)d_in[7];
    const bf16* B_Wo = (const bf16*)d_in[8];
    bf16* out = (bf16*)d_out;

    static EncodeFn enc = nullptr;
    static void *p_ox, *p_qkv, *p_oA, *p_xch;
    if (!enc) {
        void* fn = nullptr; cudaDriverEntryPointQueryResult qr;
        cudaGetDriverEntryPoint("cuTensorMapEncodeTiled", &fn, cudaEnableDefault, &qr);
        enc = (EncodeFn)fn;
        cudaFuncSetAttribute(chain_kernel, cudaFuncAttributeMaxDynamicSharedMemorySize, CHAIN_SMEM);
        cudaFuncSetAttribute(side_kernel, cudaFuncAttributeMaxDynamicSharedMemorySize, SIDE_SMEM);
        cudaGetSymbolAddress(&p_ox, g_ox); cudaGetSymbolAddress(&p_qkv, g_qkvA); cudaGetSymbolAddress(&p_oA, g_oA);
        cudaGetSymbolAddress(&p_xch, g_xch);
    }
    CUtensorMap tmXA, tmXB, tmWq, tmWk, tmWv, tmWo, tmOx;
    make_map3(enc, &tmXA, B_x, DM, SEQ, 32, NX);
    make_map3(enc, &tmXB, B_x, DM, SEQ, 32, 1);
    make_map(enc, &tmWq, B_Wq, HE, DM, 64, 128);
    make_map(enc, &tmWk, B_Wk, HE, DM, 64, 128);
    make_map(enc, &tmWv, B_Wv, HE, DM, 64, 128);
    make_map3(enc, &tmWo, B_Wo, DM, HE, 64, 7, 32);
    SideParams sp;
    sp.out = out;
    make_map3(enc, &sp.a[JV], B_Wv, HE, DM, 64, 2);
    make_map3(enc, &sp.a[JQ], A_wqkv, 3 * DM, DM, 64, 2);
    make_map3(enc, &sp.a[JP], A_wo, DM, DM, 64, 2);
    make_map3(enc, &sp.a[JO], B_Wo, DM, HE, 64, 2);
    const void* act[4] = {B_x, A_x, p_oA, p_ox};
    for (int i = 0; i < 4; i++) make_map(enc, &sp.b[i], act[i], i == JO ? HE : DM, SEQ, 64, 256);
    make_map(enc, &sp.c[0], B_x, DM, SEQ, 64, 192);
    make_map(enc, &sp.c[1], B_x, DM, SEQ, 64, 128);
    make_map(enc, &sp.c[2], p_ox, HE, SEQ, 64, 128);
    make_map(enc, &sp.c[3], p_ox, HE, SEQ, 64, 64);
    make_map(enc, &tmOx, p_ox, HE, SEQ, 64, 32);
    make_map(enc, &sp.st[0], p_qkv, 3 * DM, SEQ, 64, 256);
    make_map(enc, &sp.st[1], out, OUTW, SEQ, 64, 256);
    make_map(enc, &sp.sto, out, OUTW, SEQ, 64, 16);

    cudaStream_t st = cudaStreamPerThread;
    chain_kernel<<<96, 384, CHAIN_SMEM, st>>>(tmXA, tmXB, tmWq, tmWk, tmWv, tmWo, tmOx, B_mem0,
                                              (const char*)(((uintptr_t)p_xch + 0x1fffff) & ~(uintptr_t)0x1fffff), out);
    cudaLaunchConfig_t cfg = {};
    cfg.gridDim = dim3(NSIDE); cfg.blockDim = dim3(384); cfg.dynamicSmemBytes = SIDE_SMEM; cfg.stream = st;
    cudaLaunchAttribute at[1];
    at[0].id = cudaLaunchAttributeProgrammaticStreamSerialization; at[0].val.programmaticStreamSerializationAllowed = 1;
    cfg.attrs = at; cfg.numAttrs = 1;
    cudaLaunchKernelEx(&cfg, side_kernel, sp);
}
```
